```python
import torch

def _softmax(x, axis=-1):
    return torch.softmax(x, dim=axis)
def _gelu(x):
    return torch.nn.functional.gelu(x, approximate="tanh")
def _silu(x):
    return torch.nn.functional.silu(x)
def _sigmoid(x):
    return torch.sigmoid(x)
def _layernorm(x, axis=-1, eps=1e-5):
    m = x.mean(dim=axis, keepdim=True)
    v = x.var(dim=axis, keepdim=True, unbiased=False)
    return (x - m) / torch.sqrt(v + eps)
def _scatter_add(tgt, idx, src, axis=0):
    return tgt.clone().index_add_(axis, idx, src)
def _segment_sum(src, seg, n):
    out = torch.zeros((n,) + src.shape[1:], dtype=src.dtype)
    return out.index_add_(0, seg, src)
def _pad(x, pw):
    flat = tuple(v for pair in reversed(pw) for v in pair)
    return torch.nn.functional.pad(x, flat)

kernel_name = 'sequential_preLN__ssm_conv_s4__glu_gated_bilinear__prompt'

def setup_inputs():

    _w = (lambda a: (lambda t: t.to(torch.bfloat16) if t.is_floating_point() else t)(torch.as_tensor(a)))
    def _A_setup():
        B, L, D, N = 1, 2048, 448, 256
        A_re = -(lambda _x: torch.exp(torch.as_tensor(_x)))((lambda *s: torch.randn(*s, dtype=torch.bfloat16) * 3.2)(D, N))
        A_im = torch.pi * (lambda *s: torch.randn(*s, dtype=torch.bfloat16) * 0.05)(D, N)
        B_re = (lambda *s: torch.randn(*s, dtype=torch.bfloat16) * 0.05)(D, N)
        B_im = (lambda *s: torch.randn(*s, dtype=torch.bfloat16) * 0.05)(D, N)
        C_re = (lambda *s: torch.randn(*s, dtype=torch.bfloat16) * 0.05)(D, N)
        C_im = (lambda *s: torch.randn(*s, dtype=torch.bfloat16) * 0.05)(D, N)
        log_dt = (lambda *s: torch.randn(*s, dtype=torch.bfloat16) * 0.05)(D) * 0.5 - 4.0
        Dskip = (lambda *s: torch.randn(*s, dtype=torch.bfloat16) * 0.05)(D)
        return {
            "u": _w((lambda *s: torch.randn(*s, dtype=torch.bfloat16) * 0.05)(B, L, D)),
            "A_re": _w(A_re),
            "A_im": _w(A_im),
            "B_re": _w(B_re),
            "B_im": _w(B_im),
            "C_re": _w(C_re),
            "C_im": _w(C_im),
            "log_dt": _w(log_dt),
            "Dskip": _w(Dskip),
        }
    _A_in = _A_setup()

    def _B_setup():
        B, S, D, F = 1, 2048, 448, 1792
        return {
            "x": _w((lambda *s: torch.randn(*s, dtype=torch.bfloat16) * 0.05)(B, S, D)),
            "w_gate": _w((lambda *s: torch.randn(*s, dtype=torch.bfloat16) * 0.4)(D, F) * (D ** -0.5)),
            "w_up": _w((lambda *s: torch.randn(*s, dtype=torch.bfloat16) * 0.4)(D, F) * (D ** -0.5)),
            "w_down": _w((lambda *s: torch.randn(*s, dtype=torch.bfloat16) * 0.4)(F, D) * (F ** -0.5)),
        }
    _B_in = _B_setup()

    return {
        "A_u": _A_in["u"],
        "A_A_re": _A_in["A_re"],
        "A_A_im": _A_in["A_im"],
        "A_B_re": _A_in["B_re"],
        "A_B_im": _A_in["B_im"],
        "A_C_re": _A_in["C_re"],
        "A_C_im": _A_in["C_im"],
        "A_log_dt": _A_in["log_dt"],
        "A_Dskip": _A_in["Dskip"],
        "B_x": _B_in["x"],
        "B_w_gate": _B_in["w_gate"],
        "B_w_up": _B_in["w_up"],
        "B_w_down": _B_in["w_down"],
    }

def reference(A_u, A_A_re, A_A_im, A_B_re, A_B_im, A_C_re, A_C_im, A_log_dt, A_Dskip, B_x, B_w_gate, B_w_up, B_w_down):
    def _A_ref(u, A_re, A_im, B_re, B_im, C_re, C_im, log_dt, Dskip):
        Bsz, L, D = u.shape
        dt = torch.exp(log_dt)[:, None]
        A = A_re + 1j * A_im
        Bc = B_re + 1j * B_im
        Cc = C_re + 1j * C_im
        logdA = dt * A
        dB = dt * Bc
        l = (lambda x, dt: x.to(dt))(torch.arange(L), A_re.dtype)
        P = torch.exp(logdA[:, :, None] * l[None, None, :])
        K = torch.einsum("dn,dnl,dn->dl", Cc, P, dB).real
        L2 = 2 * L
        Kp = _pad(K, ((0, 0), (0, L)))
        up = (lambda x, *d: x.permute(*d))(u, 0, 2, 1)
        up = _pad(up, ((0, 0), (0, 0), (0, L)))
        Kf = (lambda x, axes=(-2,-1): torch.fft.rfft2(x.float(), dim=axes))(Kp[:, None, :], axes=(-2, -1))
        Uf = (lambda x, axes=(-2,-1): torch.fft.rfft2(x.float(), dim=axes))(up[:, :, None, :], axes=(-2, -1))
        Yf = Uf * Kf[None, :, :, :]
        y = (lambda x, s, axes=(-2,-1): torch.fft.irfft2(x, s=s, dim=axes).to(torch.bfloat16))(Yf, (1, L2), axes=(-2, -1))[:, :, 0, :L]
        y = (lambda x, *d: x.permute(*d))(y, 0, 2, 1) + u * Dskip[None, None, :]
        return y

    def _B_ref(x, w_gate, w_up, w_down):
        g = torch.einsum("bsd,df->bsf", x, w_gate)
        u = torch.einsum("bsd,df->bsf", x, w_up)
        h = g * u
        return torch.einsum("bsf,fd->bsd", h, w_down)

    x = A_u
    h = x + _A_ref(_layernorm(x, axis=-1), A_A_re, A_A_im, A_B_re, A_B_im, A_C_re, A_C_im, A_log_dt, A_Dskip)
    h2 = h + _B_ref(_layernorm(h, axis=-1), B_w_gate, B_w_up, B_w_down)
    return h2
```

```cpp
#include <cuda_runtime.h>
#include <cuda_bf16.h>
#include <cuda.h>
#include <stdint.h>
#include <string.h>

constexpr int L_ = 2048, D_ = 448, NM = 256, F_ = 1792;
constexpr int NCTA = 128, NCONV = 112, NTHR = 384;
constexpr uint32_t SPIN_LIMIT = 1u << 20;

constexpr int SM_A = 0;
constexpr int SM_RING = 114688;
constexpr int STAGE = 28672;
constexpr int SM_MB0 = 200704;
constexpr int SM_MB1 = 217088;
constexpr int SM_CS = 229376;
constexpr int SM_M2 = SM_CS + 1792;
constexpr int SM_RS2 = SM_M2 + 512;
constexpr int SM_RED = SM_RS2;
constexpr int SM_BAR = SM_RS2 + 512;
constexpr int SM_WRK = SM_BAR + 192;
constexpr int SM_TOTAL = SM_BAR + 256;
constexpr int B_EMPTY = 0, B_CH = 3, B_FREE = 5, B_FULL = 6, B_AFULL = 10, B_AUX = 14, B_MBF0 = 15, B_MBF1 = 16, B_WD = 17, B_XT = 18, B_WD2 = 19, B_COUNT = 20, B_X = 20;
__host__ __device__ constexpr int st_slot(int i) { return i < 4 ? i : (i < 14 ? (i - 4) % 3 : (i == 14 ? 4 : (i == 21 ? 1 : ((i & 1) ? 4 + (i - 13) / 2 : (i - 14) / 2 % 3)))); }
__host__ __device__ constexpr int st_use(int i) { int n = st_slot(i) >= 4 ? 1 : 0; for (int j = 0; j < i; j++) if (st_slot(j) == st_slot(i)) n++; return n; }
__host__ __device__ constexpr int st_addr(int i) { return st_slot(i) < 4 ? SM_RING + st_slot(i) * STAGE : SM_A + (st_slot(i) - 4) * STAGE; }
__host__ __device__ constexpr int st_dep(int i) { return i < 4 ? -1 : (i < 7 ? i - 4 : (i < 14 ? i - 3 : (i == 21 ? 16 : (i == 14 ? 11 : 10 + (i - 13) / 2)))); }
__host__ __device__ constexpr bool st_rel(int i) { for (int j = 0; j < 22; j++) if (st_dep(j) == i) return true; return false; }
constexpr uint64_t st_pack(int base) {
  uint64_t v = 0;
  for (int k = 0; k < 10; k++) {
    const int i = base + k, d = st_dep(i);
    const uint64_t e = (uint64_t)st_slot(i) | ((uint64_t)(d < 0 ? 3 : st_slot(d)) << 3) | ((uint64_t)(d < 0 ? 0 : (st_use(d) & 1)) << 5);
    v |= e << (6 * k);
  }
  return v;
}
constexpr uint64_t ST_P0 = st_pack(2), ST_P1 = st_pack(12);

constexpr int FAR_B30 = 0, FAR_U2 = 224, FAR_U6 = 448, FAR_B34 = 673, FAR_B5 = 897, FAR_U5 = 1089, FAR_B7 = 1217, FAR_B9 = 1345;
constexpr int TAB_ODD = 2112, TAB_CH = 4224;
constexpr int SM_TAB = 0;
constexpr int SM_FAR = TAB_CH;
constexpr int SM_STG = SM_RING;
constexpr int TR_PITCH = 928;
constexpr int SM_TRC = SM_FAR, SM_TRS = 200704;
constexpr int SM_WDI = 207872;
constexpr int SM_CMB = SM_WDI + 14336;
constexpr int U_PAD = 40;
constexpr int U_CH = (256 + U_PAD + 2) * 16;
constexpr int X_CH = 4096 + 32;
constexpr int SM_U = SM_RING + 2 * STAGE;
constexpr int SM_X = SM_U + 4 * U_CH + 64;
static_assert(SM_FAR + 1474 * 16 <= STAGE, "far");
static_assert(SM_X + 4 * X_CH <= SM_WDI, "ux");
static_assert(SM_TOTAL <= 232448, "smem");

constexpr int T_F0 = 0, T_B30 = 288, T_U2 = 352, T_U6 = 416, T_B34 = 480, T_B5 = 608, T_U5 = 704, T_B7 = 736, T_B9 = 880;

constexpr int rnd_bf16(int j) {
  if (j <= 256) return j;
  int sh = j < 512 ? 1 : (j < 1024 ? 2 : (j < 2048 ? 3 : 4));
  int q = j >> sh, r = j & ((1 << sh) - 1), h = 1 << (sh - 1);
  if (r > h || (r == h && (q & 1))) q++;
  return q << sh;
}
constexpr int ksrc(int tap) {
  int e = rnd_bf16(tap), i = 0, j = (e & 255) >> 3;
  if (e < 256) i = e & 7;
  else if (e < 512) i = 8 + ((e & 7) >> 1);
  else if (e < 1024) i = 12 + 2 * ((e - 512) >> 8) + ((e & 7) >> 2);
  else i = 16 + ((e - 1024) >> 8);
  return i * 36 + j;
}
struct Lut { uint32_t v[768]; };
constexpr Lut make_lut() {
  Lut t{};
  int n = 0;
  for (int j = 0; j <= 262; j++) t.v[n++] = ksrc(j) | ((T_F0 + 272 - j) << 10);
  for (int m = 32; m < 64; m++) t.v[n++] = ksrc(8 * m + 8) | ((T_B30 + m - 16) << 10);
  for (int m = 33; m <= 64; m++) t.v[n++] = ksrc(8 * m + 2) | ((T_U2 + m - 16) << 10);
  for (int m = 33; m < 64; m++) t.v[n++] = ksrc(8 * m + 6) | ((T_U6 + m - 16) << 10);
  for (int m = 33; m <= 128; m++) t.v[n++] = ksrc(8 * m + 4) | ((T_B34 + m - 16) << 10);
  for (int m = 64; m < 128; m++) t.v[n++] = ksrc(8 * m + 8) | ((T_B5 + m - 48) << 10);
  t.v[n++] = ksrc(1024) | ((T_U5 + 128 - 112) << 10) | (1u << 20);
  for (int m = 64; m < 128; m++) t.v[n++] = ksrc(16 * m + 8) | ((T_B7 + 2 * m - 112) << 10);
  for (int m = 64; m < 128; m++) t.v[n++] = ksrc(16 * m + 16) | ((T_B9 + 2 * m - 112) << 10);
  for (; n < 768; n++) t.v[n] = 0xffffffffu;
  return t;
}
__device__ const Lut g_lut = make_lut();
struct Scratch {
  uint32_t epoch[NCTA];
  uint32_t cnt[8 * 32];
  uint2 st2[L_];
  uint2 cs[2 * F_];
  uint4 ux[NCONV * 128 * 16];
  uint4 wdp[128 * 896];
  uint4 part[NCTA * 3 * 1024];
  __nv_bfloat16 hT[D_ * L_];
};
__device__ __align__(1024) Scratch g_s;
#define PROF(k)
#define PROFW(k)
#define DEV_HT(k) (k)

__device__ __forceinline__ uint32_t smem_u32(const void* p) { return (uint32_t)__cvta_generic_to_shared(p); }
#define FRESH_IDS uint32_t b; asm volatile("mov.u32 %0, %%ctaid.x;" : "=r"(b)); \
  const int rt = b >> 3, f = b & 7, ra = f & 1, sp = f >> 1; const bool conv_cta = b < NCONV; (void)rt; (void)sp; (void)ra; (void)conv_cta;
__device__ __forceinline__ void mbar_init(uint32_t b, int c) { asm volatile("mbarrier.init.shared::cta.b64 [%0], %1;" ::"r"(b), "r"(c)); }
__device__ __forceinline__ void mbar_expect(uint32_t b, uint32_t bytes) {
  asm volatile("mbarrier.arrive.expect_tx.shared::cta.b64 _, [%0], %1;" ::"r"(b), "r"(bytes) : "memory");
}
__device__ __forceinline__ void mbar_arrive(uint32_t b) { asm volatile("mbarrier.arrive.shared::cta.b64 _, [%0];" ::"r"(b) : "memory"); }
__device__ __forceinline__ void mbar_arrive_remote(uint32_t b) {
  asm volatile("mbarrier.arrive.shared::cluster.b64 _, [%0];" ::"r"(b) : "memory");
}
__device__ __forceinline__ void mbar_wait(uint32_t b, uint32_t ph) {
  asm volatile("{.reg .pred p; .reg .u32 c; mov.u32 c, 0;\n"
               "W_%=: mbarrier.try_wait.parity.shared::cta.b64 p, [%0], %1;\n"
               "@p bra D_%=;\n add.u32 c, c, 1;\n setp.lt.u32 p, c, %2;\n @p bra W_%=;\n D_%=: }"
               ::"r"(b), "r"(ph), "n"(SPIN_LIMIT) : "memory");
}
#define SPIN_CHECK(it) if (++(it) > SPIN_LIMIT) break
__device__ __forceinline__ void tma2d(uint32_t dst, const CUtensorMap* m, int c0, int c1, uint32_t bar) {
  asm volatile("cp.async.bulk.tensor.2d.shared::cluster.global.mbarrier::complete_tx::bytes [%0], [%1, {%3, %4}], [%2];"
               ::"r"(dst), "l"(m), "r"(bar), "r"(c0), "r"(c1) : "memory");
}
__device__ __forceinline__ void tma3d(uint32_t dst, const CUtensorMap* m, int c0, int c1, int c2, uint32_t bar) {
  asm volatile("cp.async.bulk.tensor.3d.shared::cluster.global.mbarrier::complete_tx::bytes [%0], [%1, {%3, %4, %5}], [%2];"
               ::"r"(dst), "l"(m), "r"(bar), "r"(c0), "r"(c1), "r"(c2) : "memory");
}
__device__ __forceinline__ void bulk_ld(uint32_t dst, const void* src, uint32_t bytes, uint32_t bar) {
  asm volatile("cp.async.bulk.shared::cluster.global.mbarrier::complete_tx::bytes [%0], [%1], %2, [%3];" ::"r"(dst), "l"(src), "r"(bytes), "r"(bar) : "memory");
}
__device__ __forceinline__ void bulk_st(void* dst, uint32_t src, uint32_t bytes) {
  asm volatile("cp.async.bulk.global.shared::cta.bulk_group [%0], [%1], %2;" ::"l"(dst), "r"(src), "r"(bytes) : "memory");
}
__device__ __forceinline__ void ldsm4(uint32_t a, uint32_t& r0, uint32_t& r1, uint32_t& r2, uint32_t& r3) {
  asm volatile("ldmatrix.sync.aligned.m8n8.x4.shared.b16 {%0,%1,%2,%3}, [%4];" : "=r"(r0), "=r"(r1), "=r"(r2), "=r"(r3) : "r"(a) : "memory");
}
__device__ __forceinline__ void ldsm4t(uint32_t a, uint32_t& r0, uint32_t& r1, uint32_t& r2, uint32_t& r3) {
  asm volatile("ldmatrix.sync.aligned.m8n8.x4.trans.shared.b16 {%0,%1,%2,%3}, [%4];" : "=r"(r0), "=r"(r1), "=r"(r2), "=r"(r3) : "r"(a) : "memory");
}
__device__ __forceinline__ void stsm4(uint32_t a, uint32_t r0, uint32_t r1, uint32_t r2, uint32_t r3) {
  asm volatile("stmatrix.sync.aligned.m8n8.x4.shared.b16 [%0], {%1,%2,%3,%4};" ::"r"(a), "r"(r0), "r"(r1), "r"(r2), "r"(r3) : "memory");
}
__device__ __forceinline__ void mma16816(float (&c)[4], uint32_t a0, uint32_t a1, uint32_t a2, uint32_t a3, uint32_t b0, uint32_t b1) {
  asm volatile("mma.sync.aligned.m16n8k16.row.col.f32.bf16.bf16.f32 {%0,%1,%2,%3},{%4,%5,%6,%7},{%8,%9},{%0,%1,%2,%3};"
               : "+f"(c[0]), "+f"(c[1]), "+f"(c[2]), "+f"(c[3]) : "r"(a0), "r"(a1), "r"(a2), "r"(a3), "r"(b0), "r"(b1));
}
__device__ __forceinline__ uint32_t lds32(uint32_t a) { uint32_t v; asm volatile("ld.shared.b32 %0, [%1];" : "=r"(v) : "r"(a) : "memory"); return v; }
__device__ __forceinline__ float ldsf(uint32_t a) { float v; asm volatile("ld.shared.f32 %0, [%1];" : "=f"(v) : "r"(a) : "memory"); return v; }
__device__ __forceinline__ uint4 lds128(uint32_t a) {
  uint4 v; asm volatile("ld.shared.v4.b32 {%0,%1,%2,%3}, [%4];" : "=r"(v.x), "=r"(v.y), "=r"(v.z), "=r"(v.w) : "r"(a) : "memory"); return v;
}
__device__ __forceinline__ void sts16(uint32_t a, uint16_t v) { asm volatile("st.shared.b16 [%0], %1;" ::"r"(a), "h"(v) : "memory"); }
__device__ __forceinline__ void stsf(uint32_t a, float v) { asm volatile("st.shared.f32 [%0], %1;" ::"r"(a), "f"(v) : "memory"); }
__device__ __forceinline__ void sts64(uint32_t a, uint32_t x, uint32_t y) { asm volatile("st.shared.v2.b32 [%0], {%1,%2};" ::"r"(a), "r"(x), "r"(y) : "memory"); }
__device__ __forceinline__ void sts128(uint32_t a, uint32_t x, uint32_t y, uint32_t z, uint32_t w) {
  asm volatile("st.shared.v4.b32 [%0], {%1,%2,%3,%4};" ::"r"(a), "r"(x), "r"(y), "r"(z), "r"(w) : "memory");
}
__device__ __forceinline__ uint32_t pack2(float lo, float hi) { uint32_t r; asm("cvt.rn.bf16x2.f32 %0, %1, %2;" : "=r"(r) : "f"(hi), "f"(lo)); return r; }
__device__ __forceinline__ float blo(uint32_t v) { return __uint_as_float(v << 16); }
__device__ __forceinline__ float bhi(uint32_t v) { return __uint_as_float(v & 0xffff0000u); }
__device__ __forceinline__ float bfr(float v) { return __bfloat162float(__float2bfloat16_rn(v)); }
__device__ __forceinline__ uint32_t hsub2(uint32_t a, uint32_t b) { uint32_t r; asm("sub.rn.bf16x2 %0, %1, %2;" : "=r"(r) : "r"(a), "r"(b)); return r; }
__device__ __forceinline__ uint32_t hadd2(uint32_t a, uint32_t b) { uint32_t r; asm("add.rn.bf16x2 %0, %1, %2;" : "=r"(r) : "r"(a), "r"(b)); return r; }
__device__ __forceinline__ uint32_t hmul2(uint32_t a, uint32_t b) { uint32_t r; asm("mul.rn.bf16x2 %0, %1, %2;" : "=r"(r) : "r"(a), "r"(b)); return r; }
__device__ __forceinline__ uint32_t hfma2(uint32_t a, uint32_t b, uint32_t c) { uint32_t r; asm("fma.rn.bf16x2 %0, %1, %2, %3;" : "=r"(r) : "r"(a), "r"(b), "r"(c)); return r; }
__device__ __forceinline__ uint4 ld_relaxed16(const void* p) {
  unsigned long long a, b;
  asm volatile("ld.relaxed.gpu.global.v2.b64 {%0,%1}, [%2];" : "=l"(a), "=l"(b) : "l"(p) : "memory");
  return make_uint4((uint32_t)a, (uint32_t)(a >> 32), (uint32_t)b, (uint32_t)(b >> 32));
}
__device__ __forceinline__ uint4 ld_relaxed_b128(const void* p) {
  uint4 v;
  asm volatile("{.reg .b128 t; ld.relaxed.gpu.global.b128 t, [%4]; mov.b128 {%0,%1,%2,%3}, t;}" : "=r"(v.x), "=r"(v.y), "=r"(v.z), "=r"(v.w) : "l"(p) : "memory");
  return v;
}
__device__ __forceinline__ void st_relaxed_b128(void* p, uint32_t x, uint32_t y, uint32_t z, uint32_t w) {
  asm volatile("{.reg .b128 t; mov.b128 t, {%1,%2,%3,%4}; st.relaxed.gpu.global.b128 [%0], t;}" ::"l"(p), "r"(x), "r"(y), "r"(z), "r"(w) : "memory");
}
__device__ __forceinline__ void st_relaxed8(void* p, uint32_t x, uint32_t y) {
  unsigned long long v = ((unsigned long long)y << 32) | x;
  asm volatile("st.relaxed.gpu.global.b64 [%0], %1;" ::"l"(p), "l"(v) : "memory");
}
__device__ __forceinline__ void wg_fence() { asm volatile("wgmma.fence.sync.aligned;" ::: "memory"); }
__device__ __forceinline__ void wg_commit() { asm volatile("wgmma.commit_group.sync.aligned;" ::: "memory"); }
template <int N> __device__ __forceinline__ void wg_wait() { asm volatile("wgmma.wait_group.sync.aligned %0;" ::"n"(N) : "memory"); }
template <int N> __device__ __forceinline__ void reg_fence(float (&d)[N]) {
#pragma unroll
  for (int i = 0; i < N; i++) asm volatile("" : "+f"(d[i])::"memory");
}
constexpr uint32_t DESC_HI128 = (1024u >> 4) | (1u << 30), DESC_HI64 = (512u >> 4) | (2u << 30);
template <uint32_t BHI, int SC> __device__ __forceinline__ void wgmma_ss_n128(float (&d)[64], uint32_t alo, uint32_t blo) {
  asm volatile("{.reg .b64 da, db; mov.b64 da, {%64, %66}; mov.b64 db, {%65, %67};\n"
    "wgmma.mma_async.sync.aligned.m64n128k16.f32.bf16.bf16 {%0,%1,%2,%3,%4,%5,%6,%7,%8,%9,%10,%11,%12,%13,%14,%15,%16,%17,%18,%19,%20,%21,%22,%23,%24,%25,%26,%27,%28,%29,%30,%31,%32,%33,%34,%35,%36,%37,%38,%39,%40,%41,%42,%43,%44,%45,%46,%47,%48,%49,%50,%51,%52,%53,%54,%55,%56,%57,%58,%59,%60,%61,%62,%63}, da, db, %68, 1, 1, 1, 1;}"
    : "+f"(d[0]),"+f"(d[1]),"+f"(d[2]),"+f"(d[3]),"+f"(d[4]),"+f"(d[5]),"+f"(d[6]),"+f"(d[7]),"+f"(d[8]),"+f"(d[9]),"+f"(d[10]),"+f"(d[11]),"+f"(d[12]),"+f"(d[13]),"+f"(d[14]),"+f"(d[15]),"+f"(d[16]),"+f"(d[17]),"+f"(d[18]),"+f"(d[19]),"+f"(d[20]),"+f"(d[21]),"+f"(d[22]),"+f"(d[23]),"+f"(d[24]),"+f"(d[25]),"+f"(d[26]),"+f"(d[27]),"+f"(d[28]),"+f"(d[29]),"+f"(d[30]),"+f"(d[31]),"+f"(d[32]),"+f"(d[33]),"+f"(d[34]),"+f"(d[35]),"+f"(d[36]),"+f"(d[37]),"+f"(d[38]),"+f"(d[39]),"+f"(d[40]),"+f"(d[41]),"+f"(d[42]),"+f"(d[43]),"+f"(d[44]),"+f"(d[45]),"+f"(d[46]),"+f"(d[47]),"+f"(d[48]),"+f"(d[49]),"+f"(d[50]),"+f"(d[51]),"+f"(d[52]),"+f"(d[53]),"+f"(d[54]),"+f"(d[55]),"+f"(d[56]),"+f"(d[57]),"+f"(d[58]),"+f"(d[59]),"+f"(d[60]),"+f"(d[61]),"+f"(d[62]),"+f"(d[63])
    : "r"(alo), "r"(blo), "n"(DESC_HI128), "n"(BHI), "n"(SC));
}
template <uint32_t BHI, int SC> __device__ __forceinline__ void wgmma_ss_n64(float (&d)[32], uint32_t alo, uint32_t blo) {
  asm volatile("{.reg .b64 da, db; mov.b64 da, {%32, %34}; mov.b64 db, {%33, %35};\n"
    "wgmma.mma_async.sync.aligned.m64n64k16.f32.bf16.bf16 {%0,%1,%2,%3,%4,%5,%6,%7,%8,%9,%10,%11,%12,%13,%14,%15,%16,%17,%18,%19,%20,%21,%22,%23,%24,%25,%26,%27,%28,%29,%30,%31}, da, db, %36, 1, 1, 1, 1;}"
    : "+f"(d[0]),"+f"(d[1]),"+f"(d[2]),"+f"(d[3]),"+f"(d[4]),"+f"(d[5]),"+f"(d[6]),"+f"(d[7]),"+f"(d[8]),"+f"(d[9]),"+f"(d[10]),"+f"(d[11]),"+f"(d[12]),"+f"(d[13]),"+f"(d[14]),"+f"(d[15]),"+f"(d[16]),"+f"(d[17]),"+f"(d[18]),"+f"(d[19]),"+f"(d[20]),"+f"(d[21]),"+f"(d[22]),"+f"(d[23]),"+f"(d[24]),"+f"(d[25]),"+f"(d[26]),"+f"(d[27]),"+f"(d[28]),"+f"(d[29]),"+f"(d[30]),"+f"(d[31])
    : "r"(alo), "r"(blo), "n"(DESC_HI128), "n"(BHI), "n"(SC));
}
template <int SC> __device__ __forceinline__ void wgmma_rs_n56(float (&d)[28], uint32_t a0, uint32_t a1, uint32_t a2, uint32_t a3, uint32_t blo) {
  asm volatile("{.reg .b64 db; mov.b64 db, {%32, %33};\n"
    "wgmma.mma_async.sync.aligned.m64n56k16.f32.bf16.bf16 {%0,%1,%2,%3,%4,%5,%6,%7,%8,%9,%10,%11,%12,%13,%14,%15,%16,%17,%18,%19,%20,%21,%22,%23,%24,%25,%26,%27}, {%28,%29,%30,%31}, db, %34, 1, 1, 1;}"
    : "+f"(d[0]),"+f"(d[1]),"+f"(d[2]),"+f"(d[3]),"+f"(d[4]),"+f"(d[5]),"+f"(d[6]),"+f"(d[7]),"+f"(d[8]),"+f"(d[9]),"+f"(d[10]),"+f"(d[11]),"+f"(d[12]),"+f"(d[13]),"+f"(d[14]),"+f"(d[15]),"+f"(d[16]),"+f"(d[17]),"+f"(d[18]),"+f"(d[19]),"+f"(d[20]),"+f"(d[21]),"+f"(d[22]),"+f"(d[23]),"+f"(d[24]),"+f"(d[25]),"+f"(d[26]),"+f"(d[27])
    : "r"(a0), "r"(a1), "r"(a2), "r"(a3), "r"(blo), "n"(DESC_HI128), "n"(SC));
}

struct Params {
  const __nv_bfloat16 *x, *Are, *Aim, *Bre, *Bim, *Cre, *Cim, *logdt, *dskip;
  Scratch* s;
  const uint32_t* lut;
  __nv_bfloat16* out;
  long long* prof;
  uint32_t zero;
};

struct cf { float r, i; };
__device__ __forceinline__ cf cmul(cf a, cf b) { cf c; c.r = fmaf(a.r, b.r, -a.i * b.i); c.i = fmaf(a.r, b.i, a.i * b.r); return c; }
__device__ __forceinline__ cf cexp_e(float a2, float th, float tl, float e) {
  float t = th * e;
  float r = (t - rintf(t)) + tl * e;
  float ang = r * 6.283185307179586f;
  float mag;
  asm("ex2.approx.ftz.f32 %0, %1;" : "=f"(mag) : "f"(a2 * e));
  cf z; z.r = mag * __cosf(ang); z.i = mag * __sinf(ang);
  return z;
}

template <int FAR, int TAB, int S0, int NS0, int GRP>
__device__ __forceinline__ void far_seq(float (&acc)[4][4], uint32_t fb, uint32_t gf, uint32_t z) {
  constexpr int NS = S0 + NS0 - 1 > 4 * GRP + 3 ? 4 * GRP + 4 - S0 : NS0;
  constexpr int RHI = 3 - S0, RL0 = -(S0 + NS - 1) < -4 * GRP ? -4 * GRP : -(S0 + NS - 1);
  constexpr int NB = (RHI - RL0 + 2) / 2 * 2, RLO = RHI - NB + 1;
  uint32_t H[NB][2], G[2 * NS + 1];
#pragma unroll
  for (int q = NB / 2 - 1; q >= 0; q--)
    ldsm4t(fb + (FAR + 16 * (RLO + 2 * q)) * 16, H[2 * q][0], H[2 * q][1], H[2 * q + 1][0], H[2 * q + 1][1]);
#pragma unroll
  for (int k = 0; k < 2 * NS + 1; k++) G[k] = lds32(gf + TAB * 2 + k * 16);
#pragma unroll
  for (int j = 0; j < NS; j++) {
    const uint32_t a0 = j ? G[2 * j] + z : G[0], a2 = G[2 * j + 1] + z;
#pragma unroll
    for (int i = 3; i >= 0; i--) {
      const int r = i - S0 - j;
      if (r >= RL0) mma16816(acc[i], a0, G[2 * j + 1], a2, G[2 * j + 2], H[r - RLO][0], H[r - RLO][1]);
    }
  }
}
template <int GRP> __device__ __forceinline__ void far_mid(float (&acc)[4][4], uint32_t fb, uint32_t gf, uint32_t z) {
  far_seq<FAR_B30, T_B30, 2, 3, GRP>(acc, fb, gf, z);
  far_seq<FAR_U2, T_U2, 2, 3, GRP>(acc, fb, gf, z);
  far_seq<FAR_U6, T_U6, 2, 3, GRP>(acc, fb, gf, z);
  far_seq<FAR_B34, T_B34, 2, 7, GRP>(acc, fb, gf, z);
  if (GRP >= 1) far_seq<FAR_B5, T_B5, 4, 5, GRP ? GRP : 1>(acc, fb, gf, z);
}
template <int GRP> __device__ __forceinline__ void far_far(float (&acc)[4][4], uint32_t fb, uint32_t gf, uint32_t z) {
  far_seq<FAR_B7, T_B7, 8, 8, GRP>(acc, fb, gf, z);
  far_seq<FAR_U5, T_U5, 8, 1, GRP>(acc, fb, gf, z);
  far_seq<FAR_B9, T_B9, 8, 8, GRP>(acc, fb, gf, z);
}

__device__ __forceinline__ void step2_item(uint32_t sb, int wi, int lane) {
  const int it2 = wi >> 2, ch = wi & 3;
  const int c = 32 * it2 + lane - 1;
  const uint32_t ua = sb + SM_U + ch * U_CH + (U_PAD + c) * 16;
  uint2 pv;
  asm volatile("ld.shared.v2.b32 {%0,%1}, [%2];" : "=r"(pv.x), "=r"(pv.y) : "r"(ua - 8) : "memory");
  const uint4 cu = lds128(ua), nx = lds128(ua + 16);
  const uint32_t fa = sb + SM_FAR + ch * STAGE + (c + 1) * 16;
  sts128(fa + FAR_U2 * 16, cu.w, nx.x, nx.y, nx.z);
  sts128(fa + FAR_U6 * 16, cu.y, cu.z, cu.w, nx.x);
  float P[17];
  P[0] = 0.f;
  const uint32_t w8[8] = {pv.x, pv.y, cu.x, cu.y, cu.z, cu.w, nx.x, nx.y};
#pragma unroll
  for (int k = 0; k < 8; k++) { P[2 * k + 1] = P[2 * k] + blo(w8[k]); P[2 * k + 2] = P[2 * k] + (blo(w8[k]) + bhi(w8[k])); }
  uint32_t r[4];
#pragma unroll
  for (int k = 0; k < 4; k++) r[k] = pack2(P[2 * k + 6] - P[2 * k + 3], P[2 * k + 7] - P[2 * k + 4]);
  sts128(fa + FAR_B30 * 16, r[0], r[1], r[2], r[3]);
  sts64(fa + FAR_B34 * 16 - 8, r[0], r[1]);
  sts64(fa + FAR_B34 * 16, r[2], r[3]);
  if (it2 < 6) {
#pragma unroll
    for (int k = 0; k < 4; k++) r[k] = pack2(P[2 * k + 7] - P[2 * k + 2], P[2 * k + 8] - P[2 * k + 3]);
    sts128(fa + FAR_B5 * 16, r[0], r[1], r[2], r[3]);
  } else if (lane == 31) {
    sts64(fa + FAR_B34 * 16 + 8, 0, 0);
    sts128(sb + SM_FAR + ch * STAGE + FAR_B9 * 16, 0, 0, 0, 0);
  }
  if (it2 < 4) {
#pragma unroll
    for (int k = 0; k < 4; k++) r[k] = pack2(P[2 * k + 8] - P[2 * k + 1], P[2 * k + 9] - P[2 * k + 2]);
    sts128(fa + FAR_B7 * 16, r[0], r[1], r[2], r[3]);
#pragma unroll
    for (int k = 0; k < 4; k++) r[k] = pack2(P[2 * k + 9] - P[2 * k], P[2 * k + 10] - P[2 * k + 1]);
    sts128(fa + FAR_B9 * 16 + 16, r[0], r[1], r[2], r[3]);
    sts128(fa + FAR_U5 * 16, __byte_perm(cu.y, cu.z, 0x5432), __byte_perm(cu.z, cu.w, 0x5432), __byte_perm(cu.w, nx.x, 0x5432), __byte_perm(nx.x, nx.y, 0x5432));
  }
}

__global__ void __cluster_dims__(2, 1, 1) __launch_bounds__(NTHR, 1)
fused_kernel(const Params p,
             const __grid_constant__ CUtensorMap tm_wg128, const __grid_constant__ CUtensorMap tm_wu128,
             const __grid_constant__ CUtensorMap tm_wg64, const __grid_constant__ CUtensorMap tm_wu64,
             const __grid_constant__ CUtensorMap tm_wd, const __grid_constant__ CUtensorMap tm_h) {
  extern __shared__ __align__(1024) unsigned char smem[];
  const uint32_t sb = smem_u32(smem);
  const int tid = threadIdx.x, lane = tid & 31;
  const uint32_t b = blockIdx.x;
  const bool conv_cta = b < NCONV;
  PROF(0);
  const uint32_t bar = sb + SM_BAR;
  uint4 v[7];
  uint32_t lut[6], sraw;
  const size_t po = (size_t)b * 512 + 2 * tid;
  if (tid >= 256) {
    const uint4* src = (const uint4*)(p.x + (size_t)(16 * b + ((tid - 256) >> 3)) * D_) + (lane & 7);
#pragma unroll
    for (int i = 0; i < 7; i++)
      asm volatile("ld.global.nc.v4.u32 {%0,%1,%2,%3}, [%4];" : "=r"(v[i].x), "=r"(v[i].y), "=r"(v[i].z), "=r"(v[i].w) : "l"(src + 8 * i));
  } else if (conv_cta) {
    asm volatile("ld.global.nc.u32 %0, [%1];" : "=r"(v[0].x) : "l"(p.Are + po));
    asm volatile("ld.global.nc.u32 %0, [%1];" : "=r"(v[0].y) : "l"(p.Aim + po));
    asm volatile("ld.global.nc.u32 %0, [%1];" : "=r"(sraw) : "l"(p.logdt + 2 * b));
    asm volatile("ld.global.nc.u32 %0, [%1];" : "=r"(v[0].z) : "l"(p.Bre + po));
    asm volatile("ld.global.nc.u32 %0, [%1];" : "=r"(v[0].w) : "l"(p.Bim + po));
    asm volatile("ld.global.nc.u32 %0, [%1];" : "=r"(v[1].x) : "l"(p.Cre + po));
    asm volatile("ld.global.nc.u32 %0, [%1];" : "=r"(v[1].y) : "l"(p.Cim + po));
  }
  uint32_t eraw;
  asm volatile("ld.relaxed.gpu.global.u32 %0, [%1];" : "=r"(eraw) : "l"(&p.s->epoch[b]));
#define EPOCH (eraw + 1)
#define TAG ((eraw + 1) & 0xffffu)
  const int warp = __shfl_sync(~0u, tid >> 5, 0);
  const int g = lane >> 2, t = lane & 3;

  if (warp >= 8) {
    {
      const int t2 = tid - 256, iw = warp - 8;
      const uint32_t trb = sb + (conv_cta ? SM_TRC : SM_TRS);
      const uint32_t ta = trb + (t2 >> 3) * TR_PITCH + (t2 >> 6) * 16 + (lane & 7) * 16;
      const int rr = 8 * ((lane >> 1) & 1) + 2 * (lane >> 3) + (lane & 1);
      const uint32_t la = trb + rr * TR_PITCH + (rr >> 3) * 16 + ((lane >> 2) & 1) * 448 + iw * 16;
      uint4* dst = p.s->ux + ((size_t)(4 * iw + (g >> 1)) * 128 + b) * 16 + (t >> 1) * 4 + (g & 1) * 2 + (t & 1);
      if (conv_cta) {
        sts128(sb + SM_U + iw * U_CH + lane * 16, 0, 0, 0, 0);
        if (lane < U_PAD - 32) sts128(sb + SM_U + iw * U_CH + (32 + lane) * 16, 0, 0, 0, 0);
      }
      {
        float sa[4] = {0.f, 0.f, 0.f, 0.f}, q1[4] = {0.f, 0.f, 0.f, 0.f}, q2[4] = {0.f, 0.f, 0.f, 0.f};
#pragma unroll
        for (int i = 0; i < 7; i++) {
          mma16816(sa, v[i].x, v[i].y, v[i].z, v[i].w, 0x3f803f80u, 0x3f803f80u);
          mma16816(q1, v[i].x, v[i].z, v[i].y, v[i].w, v[i].x, v[i].y);
          mma16816(q2, v[i].x, v[i].z, v[i].y, v[i].w, v[i].z, v[i].w);
        }
        float s = sa[0] + sa[2];
        float qq = (g & 1) ? q1[1] + q2[3] : q1[0] + q2[2];
        qq = __shfl_sync(~0u, qq, (lane & ~3) | (g >> 1));
        s += __shfl_xor_sync(~0u, s, 4);
        qq += __shfl_xor_sync(~0u, qq, 4);
        const float mean = s * (1.f / D_);
        PROF(21);
        const float var = fmaxf(fmaf(-mean, mean, qq * (1.f / D_)), 0.f);
        const float sd = bfr(__fsqrt_rn(bfr(bfr(var) + 1e-5f)));
        const float rs = __frcp_rn(sd), rh = bfr(rs);
        const uint32_t m2 = pack2(mean, mean), rh2 = pack2(rh, rh), rl2 = pack2(rs - rh, rs - rh);
        uint32_t w[28];
#pragma unroll
        for (int i = 0; i < 7; i++) { w[4 * i] = v[i].x; w[4 * i + 1] = v[i].y; w[4 * i + 2] = v[i].z; w[4 * i + 3] = v[i].w; }
#pragma unroll
        for (int i = 0; i < 28; i++) { const uint32_t d0 = hsub2(w[i], m2); w[i] = hfma2(d0, rh2, hmul2(d0, rl2)); }
#pragma unroll
        for (int i = 0; i < 7; i++) sts128(ta + i * 128, w[4 * i], w[4 * i + 1], w[4 * i + 2], w[4 * i + 3]);
        asm volatile("bar.sync 1, 128;" ::: "memory");
#pragma unroll
        for (int i = 0; i < 7; i++) ldsm4t(la + i * 64, w[4 * i], w[4 * i + 1], w[4 * i + 2], w[4 * i + 3]);
#pragma unroll
        for (int i = 0; i < 7; i++) st_relaxed_b128(dst + (size_t)i * (16 * 128 * 16), w[4 * i], w[4 * i + 1], w[4 * i + 2], ~w[4 * i + 3]);
        asm volatile("bar.arrive 4, 384;" ::: "memory");
        asm volatile("bar.sync 1, 128;" ::: "memory");
        if (t2 == 0) asm volatile("red.relaxed.gpu.global.add.u32 [%0], 1;" ::"l"(&p.s->cnt[160]) : "memory");
      }
      PROF(1);
#pragma unroll
      for (int i = 0; i < 7; i++) sts128(ta + i * 128, v[i].x, v[i].y, v[i].z, v[i].w);
      if (lane == 0 && iw > 0) {
#pragma unroll 1
        for (int i = iw - 1; i < B_COUNT; i += 3) {
          mbar_init(bar + 8 * i, i < B_FULL ? 8 : (i == B_AUX ? 2 : (i == B_XT ? 4 : 1)));
          if (i == B_MBF0 || i == B_MBF1) mbar_expect(bar + 8 * i, i == B_MBF0 ? 16384 : 8192);
        }
        asm volatile("fence.mbarrier_init.release.cluster;" ::: "memory");
      }
      if (t2 == 0) {
        uint32_t hv, it = 0;
        do { asm volatile("ld.relaxed.gpu.global.u32 %0, [%1];" : "=r"(hv) : "l"(&p.s->cnt[160]) : "memory"); SPIN_CHECK(it); } while ((int)(hv - EPOCH * NCTA) < 0);
      }
      asm volatile("bar.sync 1, 128;" ::: "memory");
      asm volatile("barrier.cluster.arrive.relaxed.aligned;" ::: "memory");
      PROF(22);
      const uint4* src2 = p.s->ux + (size_t)b * 2048 + (t2 >> 3) * 16 + (t2 & 7);
      uint32_t da = sb + SM_U + ((t2 >> 1) & 3) * U_CH + (U_PAD + 2 * (t2 >> 3) + (t2 & 1)) * 16;
#pragma unroll 1
      for (int a2 = 0; a2 < 2; a2++) {
        uint32_t it = 0;
        uint4 sv[8];
        bool ok;
        const bool rcv = conv_cta;
        do {
          ok = true;
          if (rcv) {
#pragma unroll
            for (int i = 0; i < 8; i++) sv[i] = ld_relaxed_b128(src2 + i * 256);
          }
          if (a2 == 0 && it == 0) {
#pragma unroll
            for (int i = 0; i < 7; i++) ldsm4t(la + i * 64, v[i].x, v[i].y, v[i].z, v[i].w);
          }
          if (!rcv) break;
#pragma unroll
          for (int i = 0; i < 8; i++) ok = ok && sv[i].w != 0;
          SPIN_CHECK(it);
        } while (!ok);
        if (rcv) {
#pragma unroll
          for (int i = 0; i < 8; i++) sts128(da + i * 512, sv[i].x, sv[i].y, sv[i].z, ~sv[i].w);
        }
        if (a2 == 0) {
#pragma unroll
          for (int i = 0; i < 7; i++) st_relaxed_b128(dst + (size_t)i * (16 * 128 * 16) + 8, v[i].x, v[i].y, v[i].z, max(~v[i].w, 1u));
          PROF(23);
          if (!rcv) break;
          asm volatile("bar.sync 1, 128;" ::: "memory");
#pragma unroll 1
          for (int k = iw >> 1; k < 7; k += 2) step2_item(sb, 4 * k + (iw & 1), lane);
          asm volatile("bar.arrive 6, 256;" ::: "memory");
          asm volatile("bar.arrive 7, 256;" ::: "memory");
          PROF(24);
          src2 += 8;
          da = sb + SM_X + ((t2 >> 1) & 3) * X_CH + (2 * (t2 >> 3) + (t2 & 1)) * 16;
        } else {
          __syncwarp();
          if (lane == 0) mbar_arrive(bar + 8 * B_XT);
          PROF(30);
#pragma unroll 1
          for (int k = (iw >> 1) ^ 1; k < 7; k += 2) step2_item(sb, 4 * k + 2 + (iw & 1), lane);
        }
      }
      asm volatile("fence.proxy.async.shared::cta;" ::: "memory");
      if (conv_cta) { asm volatile("bar.arrive 4, 256;" ::: "memory"); asm volatile("bar.arrive 5, 256;" ::: "memory"); }
      PROF(25);
    }
    asm volatile("setmaxnreg.dec.sync.aligned.u32 40;");
    FRESH_IDS
    if (!conv_cta) asm volatile("bar.sync 0, 384;" ::: "memory");
    else if (warp == 8) asm volatile("bar.sync 0, 288;" ::: "memory");
    if (warp == 8) {
      const int i = lane;
      const uint32_t e = i < 2 ? (24u | i) : (uint32_t)((i < 12 ? ST_P0 : ST_P1) >> ((6 * (i < 12 ? i - 2 : i - 12)) & 63));
      const uint32_t slot = e & 7, dsl = (e >> 3) & 3;
      const uint32_t dst = sb + (slot < 4 ? SM_RING + slot * STAGE : SM_A + (slot - 4) * STAGE), fb = bar + 8 * (B_FULL + slot);
      const bool n64 = i == 7 || i == 1;
      const int col = 224 * f + (n64 ? 192 * (ra ^ 1) : 32 * ra + 64 * ((0xaa50140u >> ((2 * i) & 31)) & 3));
      const int q = (0xe4eb910u >> ((2 * i) & 31)) & 3;
      const int k = i - 14;
      const int half = k < 4 ? (k >> 1) : (k & 1), xm = k < 4 ? (2 | (k & 1)) : (k < 6 ? 1 : 0);
      const uint4* s0 = p.s->wdp + ((4 * ra + (sp ^ xm)) * 16 + half + 2 * f) * 896;
      const CUtensorMap* mg = n64 ? &tm_wg64 : &tm_wg128;
#pragma unroll 1
      for (int st = 0; st < 22; st++) {
        if (lane == st) {
          if (st == 2 && conv_cta) mbar_wait(bar + 8 * (B_CH + 1), 0);
          if (st == 3) mbar_wait(bar + 8 * B_WD2, 0);
          if (dsl < 3) mbar_wait(bar + 8 * (B_EMPTY + dsl), (e >> 5) & 1);
          mbar_expect(fb, STAGE);
          if (st < 14) {
            tma2d(dst, mg, col, 112 * q, fb);
            tma2d(dst + 14336, mg + 1, col, 112 * q, fb);
          } else {
            asm volatile("fence.proxy.async.global;" ::: "memory");
            bulk_ld(dst, s0, 14336, fb);
            bulk_ld(dst + 14336, s0 + (ra ? -2 * 896 : 2 * 896), 14336, fb);
          }
        }
        if (st == 3) {
          uint32_t cv, it = 0;
          do { asm volatile("ld.acquire.gpu.global.u32 %0, [%1];" : "=r"(cv) : "l"(&p.s->cnt[128]) : "memory"); SPIN_CHECK(it); } while ((int)(cv - EPOCH * NCTA) < 0);
        }
        __syncwarp();
      }
    } else if (warp == 9) {
      if (lane == 0) {
#pragma unroll 1
        for (int c = 0; c < 2; c++) {
          if (conv_cta) {
            mbar_wait(bar + 8 * (B_CH + c), 0);
            asm volatile("red.release.gpu.global.add.u32 [%0], 1;" ::"l"(&p.s->cnt[32 * c]) : "memory");
            PROFW(26 + c);
          }
          uint32_t cv, it = 0;
          do { asm volatile("ld.acquire.gpu.global.u32 %0, [%1];" : "=r"(cv) : "l"(&p.s->cnt[32 * c]) : "memory"); SPIN_CHECK(it); } while ((int)(cv - EPOCH * NCONV) < 0);
          asm volatile("fence.proxy.async.global;" ::: "memory");
#pragma unroll 1
          for (int q = 2 * c; q < 2 * c + 2; q++) {
            const uint32_t ab = bar + 8 * (B_AFULL + q);
            mbar_expect(ab, STAGE);
            tma2d(sb + SM_A + q * STAGE, &tm_h, 128 * rt, 112 * q, ab);
            tma2d(sb + SM_A + q * STAGE + 14336, &tm_h, 128 * rt + 64, 112 * q, ab);
          }
          PROFW(28 + c);
        }
      }
      __syncwarp();
      if (conv_cta) {
        uint4* z = p.s->ux + (size_t)b * 2048 + lane;
#pragma unroll 1
        for (int i = 0; i < 64; i++) { z[i * 32] = make_uint4(0, 0, 0, 0); __nanosleep(70); }
      }
    } else {
      const int ww = warp - 10;
      if (ww == 1) {
        if (lane == 0) {
          const int fs = (b >> 1) & 7;
          mbar_expect(bar + 8 * B_WD, 14336);
#pragma unroll 1
          for (int i = 0; i < 7; i++) {
            int lr = 112 * (b & 1) + 16 * i + 192 * ((fs & 1) ^ 1);
            if (lr >= 224) lr -= 224;
            tma2d(sb + SM_WDI + i * 2048, &tm_wd, 56 * (b >> 4), 224 * fs + lr, bar + 8 * B_WD);
          }
          mbar_wait(bar + 8 * B_WD, 0);
          bulk_st(p.s->wdp + b * 896, sb + SM_WDI, 14336);
          asm volatile("cp.async.bulk.commit_group;" ::: "memory");
          asm volatile("cp.async.bulk.wait_group.read 0;" ::: "memory");
          mbar_arrive(bar + 8 * B_WD2);
        }
        __syncwarp();
#pragma unroll 1
        for (int m = 0; m < 2; m++) if (lane < 28) {
          uint4 cv[4]; uint32_t it = 0; bool ok;
          do {
            ok = true;
#pragma unroll
            for (int k = 0; k < 4; k++) cv[k] = ld_relaxed16(&p.s->cs[m * F_ + 224 * f + 2 * lane + 56 * k]);
#pragma unroll
            for (int k = 0; k < 4; k++) ok = ok && cv[k].y == EPOCH && cv[k].w == EPOCH;
            SPIN_CHECK(it);
          } while (!ok);
#pragma unroll
          for (int k = 0; k < 4; k++) {
            int pr = lane + 28 * k + 16 * (ra ^ 1);
            if (pr >= 112) pr -= 112;
            sts64(sb + SM_CS + pr * 16 + m * 8, cv[k].x, cv[k].z);
          }
        }
        __syncwarp();
        if (lane == 0) {
          mbar_arrive(bar + 8 * B_AUX);
          asm volatile("cp.async.bulk.wait_group 0;" ::: "memory");
          asm volatile("red.release.gpu.global.add.u32 [%0], 1;" ::"l"(&p.s->cnt[128]) : "memory");
        }
        PROFW(9);
      }
      __syncwarp();
      const int kq = lane >> 1, cb = lane & 1;
      const int kl = 2 * (kq & 3) + ((kq >> 2) & 1) + 8 * (kq >> 3);
      const uint32_t aa = sb + SM_A + ww * STAGE + (f >> 2) * 14336 + kl * 128 + (((2 * (f & 3) + cb) ^ (kl & 7)) * 16);
      float sv[16];
#pragma unroll
      for (int i = 0; i < 16; i++) sv[i] = 0.f;
#pragma unroll 1
      for (int q2 = 0; q2 < 2; q2++) {
        mbar_wait(bar + 8 * (B_AFULL + ww + 2 * q2), 0);
#pragma unroll
        for (int j = 0; j < 7; j++) {
          const uint4 hv = lds128(aa + q2 * (2 * STAGE) + j * 2048);
          const uint32_t w4[4] = {hv.x, hv.y, hv.z, hv.w};
#pragma unroll
          for (int k = 0; k < 4; k++) {
            const float a = blo(w4[k]), c = bhi(w4[k]);
            sv[2 * k] += a; sv[2 * k + 1] += c;
            sv[8 + 2 * k] = fmaf(a, a, sv[8 + 2 * k]); sv[9 + 2 * k] = fmaf(c, c, sv[9 + 2 * k]);
          }
        }
      }
#pragma unroll
      for (int lv = 0; lv < 4; lv++) {
        const int h = 8 >> lv;
        const bool up = lane & (2 * h);
#pragma unroll
        for (int i = 0; i < 8; i++) if (i < h) {
          const float keep = up ? sv[i + h] : sv[i], send = up ? sv[i] : sv[i + h];
          sv[i] = keep + __shfl_xor_sync(~0u, send, 2 * h);
        }
      }
      const uint32_t tag = TAG;
      if (ww == 1) { stsf(sb + SM_RED + lane * 4, sv[0]); asm volatile("bar.arrive 1, 64;" ::: "memory"); }
      else {
        asm volatile("bar.sync 1, 64;" ::: "memory");
        const float s = sv[0] + ldsf(sb + SM_RED + lane * 4);
        const float q = __shfl_down_sync(~0u, s, 16);
        const float mean = s * (1.f / D_);
        const float var = fmaxf(q * (1.f / D_) - mean * mean, 0.f);
        const float sd = bfr(__fsqrt_rn(bfr(bfr(var) + 1e-5f)));
        const float rs = __frcp_rn(sd);
        const int row = 128 * rt + 16 * f + 8 * cb + (lane >> 1);
        if (lane < 16) st_relaxed8(&p.s->st2[row], __float_as_uint(rs * rs), (pack2(mean, 0.f) & 0xffffu) | (tag << 16));
        if (lane == 0) p.s->epoch[b] = EPOCH;
        PROFW(10);
      }
      if (ww == 1) {
        uint4 c0, c1; uint32_t it = 0;
        do { c0 = ld_relaxed16(&p.s->st2[128 * rt + 4 * lane]); c1 = ld_relaxed16(&p.s->st2[128 * rt + 4 * lane + 2]); SPIN_CHECK(it);
        } while ((c0.y >> 16) != tag || (c0.w >> 16) != tag || (c1.y >> 16) != tag || (c1.w >> 16) != tag);
        sts128(sb + SM_M2 + lane * 16, (c0.y << 16) ^ 0x80000000u, (c0.w << 16) ^ 0x80000000u, (c1.y << 16) ^ 0x80000000u, (c1.w << 16) ^ 0x80000000u);
        sts128(sb + SM_RS2 + lane * 16, c0.x, c0.z, c1.x, c1.z);
        __syncwarp();
        if (lane == 0) mbar_arrive(bar + 8 * B_AUX);
        PROFW(11);
      }
    }
  } else {
    asm volatile("barrier.cluster.arrive.relaxed.aligned;" ::: "memory");
    if (conv_cta) {
      const int wg = warp >> 2, wt = tid & 127;
#pragma unroll 1
      for (int i = wt; i < 264; i += 128) { sts128(sb + SM_TAB + wg * STAGE + 16 * i, 0, 0, 0, 0); sts128(sb + SM_TAB + (2 + wg) * STAGE + 16 * i, 0, 0, 0, 0); }
      const uint32_t stg = sb + SM_STG + warp * 7168;
      const uint32_t st_a = stg + lane * 16;
      const uint32_t ld_a = stg + (((lane >> 3) & 1) * 2 + (lane >> 4)) * 512 + (lane & 7) * 16;
      const uint32_t ld_c = stg + 4096 + ((lane >> 3) & 1) * 512 + (lane >> 4) * 128 + (lane & 7) * 16;
      const uint32_t g_near = sb + SM_TAB + (T_F0 + 272 - g + 2 * t) * 2 + ((g & 1) ? TAB_ODD - 2 : 0);
      const uint32_t g_far0 = sb + SM_TAB + (1 + g + 2 * t) * 2 + ((g & 1) ? 0 : TAB_ODD - 2);
      const uint32_t z = p.zero;
      if (wg == 0) asm volatile("bar.sync 4, 384;" ::: "memory");
      else asm volatile("bar.arrive 4, 384;" ::: "memory");
      uint2 dskraw;
      asm volatile("ld.global.nc.u32 %0, [%1];" : "=r"(dskraw.x) : "l"(p.dskip + 2 * b + (lane & z)));
      asm volatile("ld.global.nc.u32 %0, [%1];" : "=r"(dskraw.y) : "l"(p.dskip + 224 + 2 * b + (lane & z)));
#pragma unroll
      for (int i = 0; i < 6; i++) asm volatile("ld.global.nc.u32 %0, [%1];" : "=r"(lut[i]) : "l"(p.lut + wt + 128 * i));
      PROF(21);
      float kacc[2][3][4];
#pragma unroll 1
      for (int ph = 0; ph < 4; ph++) {
        if ((ph & 1) == 0) {
#pragma unroll
          for (int i = 0; i < 24; i++) (&kacc[0][0][0])[i] = 0.f;
        }
        {
          const uint32_t sel = (ph & 1) ? 0x3244u : 0x1044u;
          const float dt = bfr(expf(__uint_as_float(__byte_perm(sraw, 0, warp < 4 ? 0x1044u : 0x3244u))));
          const float are = __uint_as_float(__byte_perm(v[0].x, 0, sel)), aim = __uint_as_float(__byte_perm(v[0].y, 0, sel));
          const float bre = __uint_as_float(__byte_perm(v[0].z, 0, sel)), bim = __uint_as_float(__byte_perm(v[0].w, 0, sel));
          const float cre = __uint_as_float(__byte_perm(v[1].x, 0, sel)), cim = __uint_as_float(__byte_perm(v[1].y, 0, sel));
          if (ph == 1) {
            asm volatile("ld.global.nc.u32 %0, [%1];" : "=r"(v[0].x) : "l"(p.Are + po + 224 * NM));
            asm volatile("ld.global.nc.u32 %0, [%1];" : "=r"(v[0].y) : "l"(p.Aim + po + 224 * NM));
            asm volatile("ld.global.nc.u32 %0, [%1];" : "=r"(v[0].z) : "l"(p.Bre + po + 224 * NM));
            asm volatile("ld.global.nc.u32 %0, [%1];" : "=r"(v[0].w) : "l"(p.Bim + po + 224 * NM));
            asm volatile("ld.global.nc.u32 %0, [%1];" : "=r"(v[1].x) : "l"(p.Cre + po + 224 * NM));
            asm volatile("ld.global.nc.u32 %0, [%1];" : "=r"(v[1].y) : "l"(p.Cim + po + 224 * NM));
            asm volatile("ld.global.nc.u32 %0, [%1];" : "=r"(sraw) : "l"(p.logdt + 224 + 2 * b + (lane & z)));
          }
          const float a2 = (dt * are) * 1.4426950408889634f;
          const float bb = dt * aim;
          const float th = bb * 0.15915494309189535f;
          const float tl = fmaf(bb, 0.15915494309189535f, -th) + bb * 6.4206383e-9f;
          const cf z8 = cexp_e(a2, th, tl, 8.f);
          cf z1 = cexp_e(a2, th, tl, 1.f), z256 = cexp_e(a2, th, tl, 256.f);
          z1.i = -z1.i; z256.i = -z256.i;
          cf w; { cf c = {cre, cim}, db = {dt * bre, dt * bim}; w = cmul(c, db); w.i = -w.i; }
          const cf q2 = cmul(z8, z8), q3 = cmul(q2, z8), q4 = cmul(q2, q2), q5 = cmul(q4, z8), q6 = cmul(q4, q2), q7 = cmul(q4, q3);
          const uint32_t R[4] = {pack2(1.f, z8.r), pack2(q2.r, q3.r), pack2(q4.r, q5.r), pack2(q6.r, q7.r)};
          const uint32_t I[4] = {pack2(0.f, z8.i), pack2(q2.i, q3.i), pack2(q4.i, q5.i), pack2(q6.i, q7.i)};
          sts128(st_a, R[0], R[1], R[2], R[3]);
          sts128(st_a + 512, I[0], I[1], I[2], I[3]);
          cf mm[3];
          mm[0] = cmul(q4, q4); mm[1] = cmul(mm[0], mm[0]); mm[2] = cmul(mm[1], mm[0]);
#pragma unroll
          for (int blk = 0; blk < 3; blk++) {
            const uint32_t mr = pack2(mm[blk].r, mm[blk].r), mi = pack2(mm[blk].i, mm[blk].i), ni = mi ^ 0x80008000u;
            uint32_t rr[4], ri[4];
#pragma unroll
            for (int k = 0; k < 4; k++) { rr[k] = hfma2(R[k], mr, hmul2(I[k], ni)); ri[k] = hfma2(R[k], mi, hmul2(I[k], mr)); }
            sts128(st_a + (blk * 2 + 2) * 512, rr[0], rr[1], rr[2], rr[3]);
            sts128(st_a + (blk * 2 + 3) * 512, ri[0], ri[1], ri[2], ri[3]);
          }
          __syncwarp();
          uint32_t A0[4][4], A1[4][4];
#pragma unroll
          for (int ks = 0; ks < 4; ks++) {
            ldsm4t(ld_a + ks * 128, A0[ks][0], A0[ks][1], A0[ks][2], A0[ks][3]);
            ldsm4t(ld_a + 2048 + ks * 128, A1[ks][0], A1[ks][1], A1[ks][2], A1[ks][3]);
          }
#define KG_TILE(nt) do { __syncwarp(); \
            _Pragma("unroll") for (int kp = 0; kp < 2; kp++) { uint32_t c6[4]; \
              ldsm4t(ld_c + (nt) * 1024 + kp * 256, c6[0], c6[1], c6[2], c6[3]); \
              _Pragma("unroll") for (int k2 = 0; k2 < 2; k2++) { const int ks = 2 * kp + k2; \
                mma16816(kacc[0][nt], A0[ks][0], A0[ks][1], A0[ks][2], A0[ks][3], c6[2 * k2], c6[2 * k2 + 1]); \
                mma16816(kacc[1][nt], A1[ks][0], A1[ks][1], A1[ks][2], A1[ks][3], c6[2 * k2], c6[2 * k2 + 1]); } } } while (0)
          const cf a0 = cmul(w, z256), b0 = cmul(a0, z256), z512 = cmul(z256, z256);
          const cf c0 = cmul(a0, z512), d0 = cmul(b0, z512), d1 = cmul(c0, z512), d2 = cmul(d0, z512), d3 = cmul(d1, z512), d4 = cmul(d2, z512);
          sts128(st_a + 12 * 512, pack2(d0.r, d1.r), pack2(d2.r, d3.r), pack2(d4.r, 0.f), 0);
          sts128(st_a + 13 * 512, pack2(d0.i, d1.i), pack2(d2.i, d3.i), pack2(d4.i, 0.f), 0);
          KG_TILE(2);
          const cf z2 = cmul(z1, z1);
          const cf p1 = cmul(w, z1), p2 = cmul(w, z2), p3 = cmul(p1, z2), p4 = cmul(p2, z2), p5 = cmul(p3, z2), p6 = cmul(p4, z2), p7 = cmul(p5, z2);
          sts128(st_a + 8 * 512, pack2(w.r, p1.r), pack2(p2.r, p3.r), pack2(p4.r, p5.r), pack2(p6.r, p7.r));
          sts128(st_a + 9 * 512, pack2(w.i, p1.i), pack2(p2.i, p3.i), pack2(p4.i, p5.i), pack2(p6.i, p7.i));
          KG_TILE(0);
          const cf a1 = cmul(p2, z256), a2_ = cmul(p4, z256), a3 = cmul(p6, z256), b1 = cmul(p4, z512), c1 = cmul(a2_, z512);
          sts128(st_a + 10 * 512, pack2(a0.r, a1.r), pack2(a2_.r, a3.r), pack2(b0.r, b1.r), pack2(c0.r, c1.r));
          sts128(st_a + 11 * 512, pack2(a0.i, a1.i), pack2(a2_.i, a3.i), pack2(b0.i, b1.i), pack2(c0.i, c1.i));
          KG_TILE(1);
          __syncwarp();
        }
        if (ph == 0) PROF(30);
        PROF(22 + (ph >> 1));
        if (ph & 1) {
          const uint32_t kp = stg + (2 * t * 36 + g) * 4;
#pragma unroll
          for (int mt = 0; mt < 2; mt++)
#pragma unroll
            for (int nt = 0; nt < 3; nt++)
#pragma unroll
              for (int e = 0; e < 4; e++) stsf(kp + ((nt * 8 + (e & 1)) * 36 + mt * 16 + (e >> 1) * 8) * 4, kacc[mt][nt][e]);
          asm volatile("bar.sync %0, 128;" ::"r"(2 + wg) : "memory");
#pragma unroll
          for (int r = 0; r < 6; r++) {
            const uint32_t e = lut[r];
            if (r < 5 || e != 0xffffffffu) {
              const uint32_t src = sb + SM_STG + wg * (4 * 7168) + (e & 1023) * 4, dst = sb + SM_TAB + (ph - 1 + wg) * STAGE + ((e >> 10) & 1023) * 2;
              const float vv = (ldsf(src) + ldsf(src + 7168)) + (ldsf(src + 2 * 7168) + ldsf(src + 3 * 7168));
              const uint16_t h = (uint16_t)(pack2(vv, 0.f) ^ ((e >> 5) & 0x8000u));
              sts16(dst, h); sts16(dst + TAB_ODD - 2, h);
            }
          }
          if (ph == 1) { asm volatile("bar.sync %0, 128;" ::"r"(2 + wg) : "memory"); PROF(6); }
          else {
            asm volatile("fence.proxy.async.shared::cta;" ::: "memory");
            asm volatile("bar.arrive 0, 288;" ::: "memory");
          }
          PROF(1);
        }
        if (ph < 2) continue;
        asm volatile("bar.sync %0, 256;" ::"r"(ph == 2 ? 6 + wg : 4 + wg) : "memory");
        PROF(1 + ph);
        const int rnd = ph - 2;
        const int ch = 2 * rnd + wg, hv = warp & 1;
        const bool heavy = (((warp >> 1) ^ wg) & 1) == 0;
        const int grp = heavy ? 3 - hv : hv;
        const int a0 = 4 * grp;
        const uint32_t ub = sb + SM_U + ch * U_CH + U_PAD * 16;
        const uint32_t g_far = g_far0 + ch * STAGE;
        const uint32_t fb0 = sb + SM_FAR + ch * STAGE + (16 * (lane >> 4) + 15 - (lane & 15)) * 16;
        const uint32_t cm0 = sb + SM_FAR + ch * STAGE + (hv ? FAR_U5 : FAR_B7 + 64) * 16 + lane * 16;
        const uint32_t cm1 = sb + (hv ? SM_CMB + ch * 1024 : SM_FAR + ch * STAGE + (FAR_B9 + 64) * 16) + lane * 16;
        float acc[4][4];
#pragma unroll
        for (int i = 0; i < 16; i++) (&acc[0][0])[i] = 0.f;
        if (!heavy) {
          if (hv) far_far<2>(acc, fb0 + 2048, g_far, z);
          else far_far<3>(acc, fb0 + 3072, g_far, z);
#pragma unroll
          for (int i = 0; i < 4; i++) {
            sts128((i < 2 ? cm0 : cm1) + (i & 1) * 512, __float_as_uint(acc[i][0]), __float_as_uint(acc[i][1]), __float_as_uint(acc[i][2]), __float_as_uint(acc[i][3]));
#pragma unroll
            for (int k = 0; k < 4; k++) acc[i][k] = 0.f;
          }
          asm volatile("bar.arrive %0, 64;" ::"r"(8 + 2 * ch + hv) : "memory");
        }
        {
          const uint32_t ha = ub + (16 * a0 - 33 + ((lane >> 3) & 1) * 8 + (lane >> 4) + (lane & 7)) * 16;
          const uint32_t ga = g_near + ch * STAGE;
#pragma unroll
          for (int sg = 0; sg < 4; sg++) {
            uint32_t Q[6][4], G[5][2];
#pragma unroll
            for (int q = 5; q >= 0; q--) ldsm4(ha - sg * 32 + q * 256, Q[q][0], Q[q][1], Q[q][2], Q[q][3]);
#pragma unroll
            for (int S = 0; S < 5; S++) if (S < 4 || sg == 0) { G[S][0] = lds32(ga - sg * 32 - S * 128 - 16); G[S][1] = lds32(ga - sg * 32 - S * 128); }
#pragma unroll
            for (int i = 3; i >= 0; i--) mma16816(acc[i], Q[i + 2][0], Q[i + 2][1], Q[i + 2][2], Q[i + 2][3], G[0][0], G[0][1]);
#pragma unroll
            for (int i = 3; i >= 0; i--) mma16816(acc[i], Q[i + 1][0], Q[i + 1][1], Q[i + 1][2], Q[i + 1][3], G[2][0], G[2][1]);
            if (sg == 0) {
#pragma unroll
              for (int i = 3; i >= 0; i--) mma16816(acc[i], Q[i][0], Q[i][1], Q[i][2], Q[i][3], G[4][0], G[4][1]);
            }
            uint32_t O[5][4];
#pragma unroll
            for (int q = 0; q < 5; q++) { O[q][0] = Q[q][1] + z; O[q][1] = Q[q + 1][0] + z; O[q][2] = Q[q][3] + z; O[q][3] = Q[q + 1][2] + z; }
#pragma unroll
            for (int i = 3; i >= 0; i--) mma16816(acc[i], O[i + 1][0], O[i + 1][1], O[i + 1][2], O[i + 1][3], G[1][0], G[1][1]);
#pragma unroll
            for (int i = 3; i >= 0; i--) mma16816(acc[i], O[i][0], O[i][1], O[i][2], O[i][3], G[3][0], G[3][1]);
          }
        }
        {
          const uint32_t fb = fb0 + grp * 1024;
          if (heavy) far_mid<2>(acc, fb, g_far, z);
          else if (hv) far_mid<1>(acc, fb, g_far, z);
          else far_mid<0>(acc, fb, g_far, z);
          if (heavy) {
            asm volatile("bar.sync %0, 64;" ::"r"(8 + 2 * ch + hv) : "memory");
#pragma unroll
            for (int i = 0; i < 4; i++) {
              const uint4 c4 = lds128((i < 2 ? cm0 : cm1) + (i & 1) * 512);
              acc[i][0] += __uint_as_float(c4.x); acc[i][1] += __uint_as_float(c4.y); acc[i][2] += __uint_as_float(c4.z); acc[i][3] += __uint_as_float(c4.w);
            }
          }
        }
        {
          mbar_wait(bar + 8 * B_XT, 0);
          const uint32_t dsk = __byte_perm(rnd ? dskraw.y : dskraw.x, 0, wg ? 0x3232 : 0x1010);
          uint32_t* dst = (uint32_t*)(p.s->hT + (size_t)(224 * rnd + 2 * b + wg) * L_ + 512 * grp) + lane;
#pragma unroll
          for (int i2 = 0; i2 < 2; i2++) {
            uint32_t xr[4], ur[4];
            ldsm4(ub + (16 * a0 + 32 * i2 + lane) * 16, ur[0], ur[1], ur[2], ur[3]);
            ldsm4(sb + SM_X + ch * X_CH + (16 * a0 + 32 * i2 + lane) * 16, xr[0], xr[1], xr[2], xr[3]);
#pragma unroll
            for (int k = 0; k < 4; k++) {
              const uint32_t yb = pack2(acc[2 * i2 + (k >> 1)][2 * (k & 1)], acc[2 * i2 + (k >> 1)][2 * (k & 1) + 1]);
              dst[(i2 * 4 + k) * 32] = hadd2(xr[k], hadd2(yb, hmul2(ur[k], dsk)));
            }
          }
        }
        PROF(26 + rnd);
        __syncwarp();
        if (lane == 0) mbar_arrive(bar + 8 * (B_CH + rnd));
      }
    } else {
      const int f = b & 7;
      if (tid == 224) mbar_init(bar + 8 * B_X, 1);
      asm volatile("bar.sync 4, 384;" ::: "memory");
      if (tid == 224) {
        mbar_expect(bar + 8 * B_X, 7 * STAGE);
#pragma unroll 1
        for (int i = 0; i < 14; i++) tma2d(sb + i * 14336, (b & 8) ? &tm_wu64 : &tm_wg64, 224 * f + 32 * (i >> 1), 224 * (i & 1), bar + 8 * B_X);
      }
      if (warp < 7) {
        const uint32_t a = sb + warp * STAGE + g * 64 + ((t ^ (g >> 1)) & 3) * 16;
        float s[8];
#pragma unroll
        for (int i = 0; i < 8; i++) s[i] = 0.f;
        mbar_wait(bar + 8 * B_X, 0);
#pragma unroll 4
        for (int i = 0; i < 56; i++) {
          const uint4 w4 = lds128(a + i * 512);
          s[0] += blo(w4.x); s[1] += bhi(w4.x); s[2] += blo(w4.y); s[3] += bhi(w4.y);
          s[4] += blo(w4.z); s[5] += bhi(w4.z); s[6] += blo(w4.w); s[7] += bhi(w4.w);
        }
#pragma unroll
        for (int lv = 0; lv < 3; lv++) {
          const int h = 4 >> lv;
          const bool up = lane & (4 * h);
#pragma unroll
          for (int i = 0; i < 4; i++) if (i < h) {
            const float keep = up ? s[i + h] : s[i], send = up ? s[i] : s[i + h];
            s[i] = keep + __shfl_xor_sync(~0u, send, 4 * h);
          }
        }
        st_relaxed8(&p.s->cs[(b - NCONV) * 224 + warp * 32 + t * 8 + g], __float_as_uint(s[0]), EPOCH);
      }
      asm volatile("bar.sync 0, 384;" ::: "memory");
    }
    asm volatile("setmaxnreg.inc.sync.aligned.u32 232;");
    asm volatile("barrier.cluster.wait.aligned;" ::: "memory");
    PROF(8);

    FRESH_IDS
    const int wgi = warp >> 2;
    const uint32_t dA = (((sb + SM_A + wgi * 14336) >> 4) & 0x3fff) | (1u << 16);
    const uint32_t dB = ((sb >> 4) & 0x3fff) | ((14336u >> 4) << 16);
    uint32_t peer;
    asm volatile("mapa.shared::cluster.u32 %0, %1, %2;" : "=r"(peer) : "r"(sb), "r"(ra ^ 1));
    float X[64], Y[64], Z[32];
    uint32_t ho[56], hp[56];
    float nm0 = 0.f, nm1 = 0.f;
    uint4 cs4[8];
    uint32_t res[16], rdep = 0;
    const int col0 = 224 * ra + 56 * sp;

#define STAGE_WAIT(i) mbar_wait(bar + 8 * (B_FULL + st_slot(i)), st_use(i) & 1)
#define STAGE_REL(i) do { if (st_rel(i) && lane == 0) mbar_arrive(bar + 8 * (B_EMPTY + st_slot(i)) + ((i) == 11 ? rdep : 0)); \
    if ((i) == 3 && lane == 0) mbar_arrive_remote(peer + SM_BAR + 8 * B_FREE); } while (0)
#define TURN_WAIT() asm volatile("bar.sync %0, 256;" ::"r"(6 + wgi) : "memory")
#define TURN_PASS() asm volatile("bar.arrive %0, 256;" ::"r"(7 - wgi) : "memory")
#define W128(ACC, i, q, kk, SC) wgmma_ss_n128<DESC_HI128, SC>(ACC, dA + (((q) * STAGE) >> 4) + (kk) * 128, dB + (st_addr(i) >> 4) + (kk) * 128)
#define TAIL(i) wg_commit(); if ((i) < 21 || wgi == 0) TURN_PASS(); wg_wait<0>(); STAGE_REL(i);
#define STAGE128(ACC, i, q, first) do { STAGE_WAIT(i); TURN_WAIT(); wg_fence(); W128(ACC, i, q, 0, (first) ? 0 : 1); \
    _Pragma("unroll") for (int kk = 1; kk < 7; kk++) W128(ACC, i, q, kk, 1); \
    TAIL(i) } while (0)
#define CSLOAD(NG, O) _Pragma("unroll") for (int j = 0; j < NG; j++) cs4[j] = lds128(sb + SM_CS + (2 * (O) + 4 * j + t) * 16)
#define EPI(ACC, NG, O, J0, J1) do { if ((J0) == 0) reg_fence(ACC); \
    _Pragma("unroll") for (int j = (J0); j < (J1) && j < NG; j++) { \
      const uint4 c4 = cs4[j]; \
      const float cg0 = __uint_as_float(c4.x), cg1 = __uint_as_float(c4.y), cu0 = __uint_as_float(c4.z), cu1 = __uint_as_float(c4.w); \
      ho[(O) + 2 * j] = pack2(fmaf(nm0, cg0, ACC[4 * j]) * fmaf(nm0, cu0, ACC[4 * NG + 4 * j]), fmaf(nm0, cg1, ACC[4 * j + 1]) * fmaf(nm0, cu1, ACC[4 * NG + 4 * j + 1])); \
      ho[(O) + 2 * j + 1] = pack2(fmaf(nm1, cg0, ACC[4 * j + 2]) * fmaf(nm1, cu0, ACC[4 * NG + 4 * j + 2]), fmaf(nm1, cg1, ACC[4 * j + 3]) * fmaf(nm1, cu1, ACC[4 * NG + 4 * j + 3])); \
    } } while (0)
#define SEND(O, NV, MB, BARI) do { \
    _Pragma("unroll") for (int vv = 0; vv < NV; vv++) \
      asm volatile("st.async.weak.shared::cluster.mbarrier::complete_tx::bytes.v4.b32 [%0], {%1,%2,%3,%4}, [%5];" \
        ::"r"(peer + (MB) + (warp * NV + vv) * 512 + lane * 16), "r"(ho[(O) + 4 * vv]), "r"(ho[(O) + 4 * vv + 1]), "r"(ho[(O) + 4 * vv + 2]), \
          "r"(ho[(O) + 4 * vv + 3]), "r"(peer + SM_BAR + 8 * (BARI)) : "memory"); } while (0)
#define RECV(O, NV, MB, BARI, PH, UNUSED) do { mbar_wait(bar + 8 * (BARI), PH); \
    _Pragma("unroll") for (int vv = 0; vv < NV; vv++) { const uint4 r4 = lds128(sb + (MB) + (warp * NV + vv) * 512 + lane * 16); \
      hp[(O) + 4 * vv] = r4.x; hp[(O) + 4 * vv + 1] = r4.y; hp[(O) + 4 * vv + 2] = r4.z; hp[(O) + 4 * vv + 3] = r4.w; } \
    } while (0)
#define REARM(O) do { const uint32_t dep = (hp[O] ^ hp[(O) + 4] ^ hp[(O) + 8] ^ hp[(O) + 12]) & p.zero;     \
      if (tid == 0) mbar_expect(bar + 8 * B_MBF0, 16384); \
      if (lane == 0) mbar_arrive_remote(peer + SM_BAR + 8 * B_FREE + dep); } while (0)
#define W64(i, hh, kk, SC) wgmma_ss_n64<DESC_HI64, SC>(Z, dA + (((2 * (hh) + (kk) / 7) * STAGE) >> 4) + ((kk) % 7) * 128, dB + (st_addr(i) >> 4) + (kk) * 64)
#define STAGE64(i, hh) do { STAGE_WAIT(i); TURN_WAIT(); wg_fence(); W64(i, hh, 0, (hh) == 0 ? 0 : 1); \
    _Pragma("unroll") for (int kk = 1; kk < 14; kk++) W64(i, hh, kk, 1); \
    TAIL(i) } while (0)

    mbar_wait(bar + 8 * (B_AFULL + 0), 0);
    if (wgi == 1) TURN_PASS();
    PROF(12);
    STAGE128(X, 0, 0, true);
    mbar_wait(bar + 8 * (B_AFULL + 1), 0);
    STAGE64(1, 0);
    STAGE128(X, 2, 1, false);
    STAGE128(Y, 3, 0, true);
    STAGE128(Y, 4, 1, false);
    PROF(31);
    mbar_wait(bar + 8 * (B_AFULL + 2), 0);
    STAGE128(X, 5, 2, false);
    mbar_wait(bar + 8 * (B_AFULL + 3), 0);
    STAGE128(X, 6, 3, false);
    STAGE64(7, 1);
    PROF(13);
    mbar_wait(bar + 8 * B_AUX, 0);
    nm0 = ldsf(sb + SM_M2 + (16 * warp + g) * 4); nm1 = ldsf(sb + SM_M2 + (16 * warp + g + 8) * 4);
    CSLOAD(8, 8);
    EPI(X, 8, 8, 0, 3);
    STAGE128(Y, 8, 2, false);
    PROF(14);
    EPI(X, 8, 8, 3, 8);
    mbar_wait(bar + 8 * B_FREE, 0);
    SEND(8, 4, SM_MB0, B_MBF0);
    CSLOAD(4, 0);
    STAGE128(Y, 9, 3, false);
    PROF(2);
    EPI(Z, 4, 0, 0, 4);
    SEND(0, 2, SM_MB1, B_MBF1);
    CSLOAD(8, 24);
    STAGE128(X, 10, 0, true);
    PROF(25);
    RECV(8, 4, SM_MB0, B_MBF0, 0, false);
#pragma unroll
    for (int j2 = 0; j2 < 4; j2++) {
      const int kl = 56 * (sp & 1) + 16 * j2 + (j2 == 3 ? 0 : (lane >> 4) * 8) + (lane & 7);
      const uint32_t addr = sb + SM_A + (2 * ra + (sp >> 1)) * STAGE + wgi * 14336 + kl * 128 + (((2 * (warp & 3) + ((lane >> 3) & 1)) ^ (lane & 7)) * 16);
      ldsm4t(addr, res[4 * j2], res[4 * j2 + 1], res[4 * j2 + 2], res[4 * j2 + 3]);
    }
    EPI(Y, 8, 24, 0, 4);
    REARM(8);
    rdep = (res[0] ^ res[4] ^ res[8] ^ res[12]) & p.zero;
    STAGE128(X, 11, 1, false);
    PROF(15);
    EPI(Y, 8, 24, 4, 8);
    mbar_wait(bar + 8 * B_FREE, 1);
    SEND(24, 4, SM_MB0, B_MBF0);
    STAGE128(X, 12, 2, false);
    RECV(0, 2, SM_MB1, B_MBF1, 0, false);
#pragma unroll
    for (int j2 = 0; j2 < 3; j2++)
      sts128(sb + SM_MB1 + (j2 < 2 ? (warp * 2 + j2) * 512 : 8192 + warp * 512) + lane * 16, res[4 * j2], res[4 * j2 + 1], res[4 * j2 + 2], res[4 * j2 + 3]);
    CSLOAD(8, 40);
    STAGE128(X, 13, 3, false);
    PROF(16);
    RECV(24, 4, SM_MB0, B_MBF0, 1, false);
    EPI(X, 8, 40, 0, 5);
    REARM(24);
    float OP[28], OQ[28];
    const uint32_t tag = TAG;
#define W56(ACC, i, half, kk) do { const int a = 4 * (7 * (half) + ((kk) % 7)); \
      const uint32_t db = dB + ((st_addr(i) + (kk) * 2048) >> 4); \
      if ((kk) == 0 && (half) == 0) wgmma_rs_n56<0>(ACC, ho[a], ho[a + 1], ho[a + 2], ho[a + 3], db); \
      else if ((kk) < 7) wgmma_rs_n56<1>(ACC, ho[a], ho[a + 1], ho[a + 2], ho[a + 3], db); \
      else wgmma_rs_n56<1>(ACC, hp[a], hp[a + 1], hp[a + 2], hp[a + 3], db); } while (0)
#define STAGE56(ACC, i, half) do { STAGE_WAIT(i); TURN_WAIT(); wg_fence(); \
    _Pragma("unroll") for (int kk = 0; kk < 14; kk++) W56(ACC, i, half, kk); \
    TAIL(i) } while (0)
#define SENDP4(ACC, XM) do { SENDP(ACC, XM, 0); SENDP(ACC, XM, 1); SENDP(ACC, XM, 2); SENDP(ACC, XM, 3); } while (0)
#define SENDP(ACC, XM, vv) do { if ((vv) == 0) reg_fence(ACC); \
    uint4* dstp = p.s->part + (size_t)(b ^ (2 * (XM))) * 3072 + ((XM) - 1) * 1024 + warp * 128 + lane; \
      st_relaxed_b128(dstp + (vv) * 32, pack2(ACC[7 * (vv)], ACC[7 * (vv) + 1]), pack2(ACC[7 * (vv) + 2], ACC[7 * (vv) + 3]), \
                      pack2(ACC[7 * (vv) + 4], ACC[7 * (vv) + 5]), (pack2(ACC[7 * (vv) + 6], 0.f) & 0xffffu) | (tag << 16)); } while (0)
    STAGE56(OP, 14, 0);
    EPI(X, 8, 40, 5, 8);
    mbar_wait(bar + 8 * B_FREE, 0);
    SEND(40, 4, SM_MB0, B_MBF0);
    STAGE56(OQ, 15, 0);
    PROF(28);
    RECV(40, 4, SM_MB0, B_MBF0, 0, false);
    PROF(29);
    STAGE56(OP, 16, 1);
    SENDP4(OP, 2);
    STAGE56(OQ, 17, 1);
    PROF(17);
    SENDP4(OQ, 3);
    STAGE56(OP, 18, 0);
    PROF(5);
    STAGE56(OP, 19, 1);
    PROF(24);
    SENDP4(OP, 1);
    STAGE56(OQ, 20, 0);
    PROF(7);
    float ps[28];
    const uint4* srcp = p.s->part + (size_t)b * 3072 + warp * 128 + lane;
    {
      uint4 pv[8]; uint32_t it = 0; bool ok;
      do {
        ok = true;
#pragma unroll
        for (int k = 0; k < 8; k++) pv[k] = ld_relaxed_b128(srcp + 1024 + (k >> 2) * 1024 + (k & 3) * 32);
#pragma unroll
        for (int k = 0; k < 8; k++) ok = ok && (pv[k].w >> 16) == tag;
        SPIN_CHECK(it);
      } while (!ok);
#pragma unroll
      for (int k = 0; k < 4; k++) {
        const int o = 7 * k;
        ps[o] = blo(pv[k].x) + blo(pv[k + 4].x); ps[o + 1] = bhi(pv[k].x) + bhi(pv[k + 4].x);
        ps[o + 2] = blo(pv[k].y) + blo(pv[k + 4].y); ps[o + 3] = bhi(pv[k].y) + bhi(pv[k + 4].y);
        ps[o + 4] = blo(pv[k].z) + blo(pv[k + 4].z); ps[o + 5] = bhi(pv[k].z) + bhi(pv[k + 4].z);
        ps[o + 6] = blo(pv[k].w) + blo(pv[k + 4].w);
      }
      __syncwarp();
    }
    PROF(19);
#pragma unroll
    for (int j2 = 0; j2 < 3; j2++) { const uint4 r4 = lds128(sb + SM_MB1 + (j2 < 2 ? (warp * 2 + j2) * 512 : 8192 + warp * 512) + lane * 16); res[4 * j2] = r4.x; res[4 * j2 + 1] = r4.y; res[4 * j2 + 2] = r4.z; res[4 * j2 + 3] = r4.w; }
    res[14] = 0; res[15] = 0;
    const float r0 = ldsf(sb + SM_RS2 + (16 * warp + g) * 4), r1 = ldsf(sb + SM_RS2 + (16 * warp + g + 8) * 4);
    STAGE56(OQ, 21, 1);
    reg_fence(OQ);
    PROF(10);
    {
      uint4 pv[4]; uint32_t it = 0; bool ok;
      do {
        ok = true;
#pragma unroll
        for (int k = 0; k < 4; k++) pv[k] = ld_relaxed_b128(srcp + k * 32);
        if (it == 0) {
#pragma unroll
          for (int i = 0; i < 28; i++) ps[i] += OQ[i];
        }
#pragma unroll
        for (int k = 0; k < 4; k++) ok = ok && (pv[k].w >> 16) == tag;
        SPIN_CHECK(it);
      } while (!ok);
#pragma unroll
      for (int k = 0; k < 4; k++) {
        const int o = 7 * k;
        ps[o] += blo(pv[k].x); ps[o + 1] += bhi(pv[k].x); ps[o + 2] += blo(pv[k].y); ps[o + 3] += bhi(pv[k].y);
        ps[o + 4] += blo(pv[k].z); ps[o + 5] += bhi(pv[k].z); ps[o + 6] += blo(pv[k].w);
      }
      __syncwarp();
    }
    PROF(11);
#pragma unroll
    for (int j = 0; j < 7; j++) {
      res[2 * j] = hadd2(res[2 * j], pack2(ps[4 * j] * r0, ps[4 * j + 1] * r0));
      res[2 * j + 1] = hadd2(res[2 * j + 1], pack2(ps[4 * j + 2] * r1, ps[4 * j + 3] * r1));
    }
    const uint32_t ost = sb + SM_MB0 + warp * 2048;
#pragma unroll
    for (int j2 = 0; j2 < 4; j2++) {
      uint32_t addr = ost + (lane & 15) * 112 + (2 * j2 + (lane >> 4)) * 16;
      if (j2 == 3 && lane >= 16) addr = ost + 1792 + (lane & 15) * 16;
      stsm4(addr, res[4 * j2], res[4 * j2 + 1], res[4 * j2 + 2], res[4 * j2 + 3]);
    }
    __syncwarp();
    char* op = (char*)p.out + (size_t)(128 * rt + 16 * warp) * (D_ * 2) + col0 * 2;
#pragma unroll
    for (int k = 0; k < 4; k++) {
      const int idx = lane + 32 * k;
      if (idx < 112) {
        const int row = (idx * 147) >> 10, c = idx - 7 * row;
        const uint4 ov = lds128(ost + idx * 16);
        *(uint4*)(op + row * (D_ * 2) + c * 16) = ov;
      }
    }
    PROF(20);
  }
}

typedef CUresult (*EncodeFn)(CUtensorMap*, CUtensorMapDataType, cuuint32_t, void*, const cuuint64_t*, const cuuint64_t*,
                             const cuuint32_t*, const cuuint32_t*, CUtensorMapInterleave, CUtensorMapSwizzle,
                             CUtensorMapL2promotion, CUtensorMapFloatOOBfill);

extern "C" void kernel_launch(void* const* d_in, const int* in_sizes, int n_in, void* d_out, int out_size) {
  (void)in_sizes; (void)n_in; (void)out_size;
  static EncodeFn enc = nullptr;
  static void *scr = nullptr, *lut = nullptr, *prof = nullptr;
  if (!enc) {
    void* fn = nullptr; cudaDriverEntryPointQueryResult qr;
    cudaGetDriverEntryPoint("cuTensorMapEncodeTiled", &fn, cudaEnableDefault, &qr);
    enc = (EncodeFn)fn;
    cudaGetSymbolAddress(&scr, g_s);
    cudaGetSymbolAddress(&lut, g_lut);
    cudaFuncSetAttribute(fused_kernel, cudaFuncAttributeMaxDynamicSharedMemorySize, SM_TOTAL);
  }
  Params p;
  p.x = (const __nv_bfloat16*)d_in[0];
  p.Are = (const __nv_bfloat16*)d_in[1]; p.Aim = (const __nv_bfloat16*)d_in[2];
  p.Bre = (const __nv_bfloat16*)d_in[3]; p.Bim = (const __nv_bfloat16*)d_in[4];
  p.Cre = (const __nv_bfloat16*)d_in[5]; p.Cim = (const __nv_bfloat16*)d_in[6];
  p.logdt = (const __nv_bfloat16*)d_in[7]; p.dskip = (const __nv_bfloat16*)d_in[8];
  p.s = (Scratch*)scr; p.lut = (const uint32_t*)lut; p.prof = (long long*)prof; p.zero = 0;
  p.out = (__nv_bfloat16*)d_out;
  CUtensorMap m[6];
  const cuuint32_t es[3] = {1, 1, 1};
  for (int i = 0; i < 4; i++) {
    const cuuint64_t dims[2] = {(cuuint64_t)F_, (cuuint64_t)D_};
    const cuuint64_t str[1] = {(cuuint64_t)F_ * 2};
    const cuuint32_t box128[2] = {64, 112}, box64[2] = {32, 224};
    enc(&m[i], CU_TENSOR_MAP_DATA_TYPE_BFLOAT16, 2, d_in[10 + (i & 1)], dims, str, i < 2 ? box128 : box64, es,
        CU_TENSOR_MAP_INTERLEAVE_NONE, i < 2 ? CU_TENSOR_MAP_SWIZZLE_128B : CU_TENSOR_MAP_SWIZZLE_64B,
        CU_TENSOR_MAP_L2_PROMOTION_L2_128B, CU_TENSOR_MAP_FLOAT_OOB_FILL_NONE);
  }
  {
    const cuuint64_t dims[2] = {(cuuint64_t)D_, (cuuint64_t)F_}; const cuuint64_t str[1] = {(cuuint64_t)D_ * 2};
    const cuuint32_t box[2] = {64, 16};
    enc(&m[4], CU_TENSOR_MAP_DATA_TYPE_BFLOAT16, 2, d_in[12], dims, str, box, es, CU_TENSOR_MAP_INTERLEAVE_NONE,
        CU_TENSOR_MAP_SWIZZLE_128B, CU_TENSOR_MAP_L2_PROMOTION_L2_128B, CU_TENSOR_MAP_FLOAT_OOB_FILL_NONE);
  }
  {
    const cuuint64_t dims[2] = {(cuuint64_t)L_, (cuuint64_t)D_}; const cuuint64_t str[1] = {(cuuint64_t)L_ * 2};
    const cuuint32_t box[2] = {64, 112};
    enc(&m[5], CU_TENSOR_MAP_DATA_TYPE_BFLOAT16, 2, (void*)p.s->hT, dims, str, box, es, CU_TENSOR_MAP_INTERLEAVE_NONE,
        CU_TENSOR_MAP_SWIZZLE_128B, CU_TENSOR_MAP_L2_PROMOTION_L2_128B, CU_TENSOR_MAP_FLOAT_OOB_FILL_NONE);
  }
  fused_kernel<<<NCTA, NTHR, SM_TOTAL, cudaStreamPerThread>>>(p, m[0], m[1], m[2], m[3], m[4], m[5]);
}
```

```cpp
#include <cuda_runtime.h>
#include <cuda_bf16.h>
#include <cuda.h>
#include <stdint.h>
#include <string.h>

constexpr int L_ = 2048, D_ = 448, NM = 256, F_ = 1792;
constexpr int NCTA = 128, NCONV = 112, NTHR = 384;
constexpr uint32_t SPIN_LIMIT = 1u << 20;

constexpr uint32_t SMEM_BASE = 0x400;
constexpr int SM_A = 0;
constexpr int SM_RING = 114688;
constexpr int STAGE = 28672;
constexpr int SM_MB0 = 200704;
constexpr int SM_MB1 = 217088;
constexpr int SM_CS = 229376;
constexpr int SM_M2 = SM_CS + 2048;
constexpr int SM_RS2 = SM_M2 + 256;
constexpr int SM_RED = SM_RS2;
constexpr int SM_BAR = SM_RS2 + 512;
constexpr int SM_TOTAL = SM_BAR + 256;
constexpr int B_EMPTY = 0, B_CH = 3, B_FREE = 5, B_FULL = 6, B_AFULL = 10, B_AUX = 14, B_MBF0 = 15, B_MBF1 = 16, B_WD = 17, B_XT = 18, B_WD2 = 19, B_WD3 = 20, B_XT2 = 21, B_X = 22;
__host__ __device__ constexpr int st_slot(int i) { return i < 4 ? i : (i < 14 ? (i - 4) % 3 : (i == 21 ? 2 : ((i & 1) ? 5 + (i - 15) / 2 : ((i - 12) / 2) % 3))); }
__host__ __device__ constexpr int st_use(int i) { int n = st_slot(i) >= 4 ? 1 : 0; for (int j = 0; j < i; j++) if (st_slot(j) == st_slot(i)) n++; return n; }
__host__ __device__ constexpr int st_addr(int i) { return st_slot(i) < 4 ? SM_RING + st_slot(i) * STAGE : SM_A + (st_slot(i) - 4) * STAGE; }
__host__ __device__ constexpr int st_dep(int i) { return i < 4 ? -1 : (i < 7 ? i - 4 : (i < 14 ? i - 3 : (i == 21 ? 16 : 11 + (i - 14) / 2))); }
__host__ __device__ constexpr bool st_rel(int i) { for (int j = 0; j < 22; j++) if (st_dep(j) == i) return true; return false; }
constexpr uint64_t st_pack(int base) {
  uint64_t v = 0;
  for (int k = 0; k < 10; k++) {
    const int i = base + k, d = st_dep(i);
    const uint64_t e = (uint64_t)st_slot(i) | ((uint64_t)(d < 0 ? 3 : st_slot(d)) << 3) | ((uint64_t)(d < 0 ? 0 : (st_use(d) & 1)) << 5);
    v |= e << (6 * k);
  }
  return v;
}
constexpr uint64_t ST_P0 = st_pack(2), ST_P1 = st_pack(12);

constexpr int FAR_B30 = 0, FAR_U2 = 224, FAR_U6 = 448, FAR_B34 = 673, FAR_B5 = 897, FAR_U5 = 1089, FAR_B7 = 1217, FAR_B9 = 1345;
constexpr int TAB_ODD = 2112, TAB_CH = 4224;
constexpr int SM_TAB = 0;
constexpr int SM_FAR = TAB_CH;
constexpr int SM_STG = SM_RING;
constexpr int TR_PITCH = 928;
constexpr int SM_TRC = SM_FAR, SM_TRS = 200704;
constexpr int SM_WDI = 207872;
constexpr int SM_CMB = SM_WDI + 14336;
constexpr int U_PAD = 40;
constexpr int U_CH = (256 + U_PAD + 2) * 16;
constexpr int X_CH = 4096 + 32;
constexpr int SM_U = SM_RING + 2 * STAGE;
constexpr int SM_X = SM_U + 4 * U_CH + 64;
static_assert(SM_FAR + 1474 * 16 <= STAGE, "far");
static_assert(SM_X + 4 * X_CH <= SM_WDI, "ux");
static_assert(SM_TOTAL <= 232448, "smem");

constexpr int T_F0 = 0, T_B30 = 288, T_U2 = 352, T_U6 = 416, T_B34 = 480, T_B5 = 608, T_U5 = 704, T_B7 = 736, T_B9 = 880;

constexpr int rnd_bf16(int j) {
  if (j <= 256) return j;
  int sh = j < 512 ? 1 : (j < 1024 ? 2 : (j < 2048 ? 3 : 4));
  int q = j >> sh, r = j & ((1 << sh) - 1), h = 1 << (sh - 1);
  if (r > h || (r == h && (q & 1))) q++;
  return q << sh;
}
constexpr int ksrc(int tap) {
  int e = rnd_bf16(tap), i = 0, j = (e & 255) >> 3;
  if (e < 256) i = e & 7;
  else if (e < 512) i = 8 + ((e & 7) >> 1);
  else if (e < 1024) i = 12 + 2 * ((e - 512) >> 8) + ((e & 7) >> 2);
  else i = 16 + ((e - 1024) >> 8);
  return i * 36 + j;
}
struct Lut { uint32_t v[768]; };
constexpr Lut make_lut() {
  Lut t{};
  int n = 0;
  for (int j = 0; j <= 262; j++) t.v[n++] = ksrc(j) | ((T_F0 + 272 - j) << 10);
  for (int m = 32; m < 64; m++) t.v[n++] = ksrc(8 * m + 8) | ((T_B30 + m - 16) << 10);
  for (int m = 33; m <= 64; m++) t.v[n++] = ksrc(8 * m + 2) | ((T_U2 + m - 16) << 10);
  for (int m = 33; m < 64; m++) t.v[n++] = ksrc(8 * m + 6) | ((T_U6 + m - 16) << 10);
  for (int m = 33; m <= 128; m++) t.v[n++] = ksrc(8 * m + 4) | ((T_B34 + m - 16) << 10);
  for (int m = 64; m < 128; m++) t.v[n++] = ksrc(8 * m + 8) | ((T_B5 + m - 48) << 10);
  t.v[n++] = ksrc(1024) | ((T_U5 + 128 - 112) << 10) | (1u << 20);
  for (int m = 64; m < 128; m++) t.v[n++] = ksrc(16 * m + 8) | ((T_B7 + 2 * m - 112) << 10);
  for (int m = 64; m < 128; m++) t.v[n++] = ksrc(16 * m + 16) | ((T_B9 + 2 * m - 112) << 10);
  for (; n < 768; n++) t.v[n] = 0xffffffffu;
  return t;
}
__device__ const Lut g_lut = make_lut();
struct Scratch {
  uint32_t epoch[NCTA];
  uint32_t cnt[8 * 32];
  uint2 st2[L_];
  uint2 cs[2 * F_];
  uint4 ux[NCONV * 128 * 16];
  uint4 wdp[128 * 784];
  uint4 part[NCTA * 3 * 1024];
  __nv_bfloat16 hT[D_ * L_];
};
__device__ __align__(1024) Scratch g_s;

__device__ __forceinline__ uint32_t smem_u32(const void* p) { return (uint32_t)__cvta_generic_to_shared(p); }
#define FRESH_IDS uint32_t b; asm volatile("mov.u32 %0, %%ctaid.x;" : "=r"(b)); \
  const int rt = b >> 3, f = b & 7, ra = f & 1, sp = f >> 1; const bool conv_cta = b < NCONV; (void)rt; (void)sp; (void)ra; (void)conv_cta;
__device__ __forceinline__ void mbar_init(uint32_t b, int c) { asm volatile("mbarrier.init.shared::cta.b64 [%0], %1;" ::"r"(b), "r"(c)); }
__device__ __forceinline__ void mbar_expect(uint32_t b, uint32_t bytes) {
  asm volatile("mbarrier.arrive.expect_tx.shared::cta.b64 _, [%0], %1;" ::"r"(b), "r"(bytes) : "memory");
}
__device__ __forceinline__ void mbar_arrive(uint32_t b) { asm volatile("mbarrier.arrive.shared::cta.b64 _, [%0];" ::"r"(b) : "memory"); }
__device__ __forceinline__ void mbar_arrive_remote(uint32_t b) {
  asm volatile("mbarrier.arrive.shared::cluster.b64 _, [%0];" ::"r"(b) : "memory");
}
__device__ __forceinline__ void mbar_wait(uint32_t b, uint32_t ph) {
  asm volatile("{.reg .pred p; .reg .u32 c; mov.u32 c, 0;\n"
               "W_%=: mbarrier.try_wait.parity.shared::cta.b64 p, [%0], %1;\n"
               "@p bra D_%=;\n add.u32 c, c, 1;\n setp.lt.u32 p, c, %2;\n @p bra W_%=;\n D_%=: }"
               ::"r"(b), "r"(ph), "n"(SPIN_LIMIT) : "memory");
}
#define SPIN_CHECK(it) if (++(it) > SPIN_LIMIT) break
__device__ __forceinline__ void tma2d(uint32_t dst, const CUtensorMap* m, int c0, int c1, uint32_t bar) {
  asm volatile("cp.async.bulk.tensor.2d.shared::cluster.global.mbarrier::complete_tx::bytes [%0], [%1, {%3, %4}], [%2];"
               ::"r"(dst), "l"(m), "r"(bar), "r"(c0), "r"(c1) : "memory");
}
__device__ __forceinline__ void tma2d_mc(uint32_t dst, const CUtensorMap* m, int c0, int c1, uint32_t bar) {
  asm volatile("cp.async.bulk.tensor.2d.shared::cluster.global.mbarrier::complete_tx::bytes.multicast::cluster [%0], [%1, {%3, %4}], [%2], %5;"
               ::"r"(dst), "l"(m), "r"(bar), "r"(c0), "r"(c1), "h"((uint16_t)3) : "memory");
}
__device__ __forceinline__ void tma3d(uint32_t dst, const CUtensorMap* m, int c0, int c1, int c2, uint32_t bar) {
  asm volatile("cp.async.bulk.tensor.3d.shared::cluster.global.mbarrier::complete_tx::bytes [%0], [%1, {%3, %4, %5}], [%2];"
               ::"r"(dst), "l"(m), "r"(bar), "r"(c0), "r"(c1), "r"(c2) : "memory");
}
__device__ __forceinline__ void bulk_ld(uint32_t dst, const void* src, uint32_t bytes, uint32_t bar) {
  asm volatile("cp.async.bulk.shared::cluster.global.mbarrier::complete_tx::bytes [%0], [%1], %2, [%3];" ::"r"(dst), "l"(src), "r"(bytes), "r"(bar) : "memory");
}
__device__ __forceinline__ void bulk_st(void* dst, uint32_t src, uint32_t bytes) {
  asm volatile("cp.async.bulk.global.shared::cta.bulk_group [%0], [%1], %2;" ::"l"(dst), "r"(src), "r"(bytes) : "memory");
}
__device__ __forceinline__ void ldsm4(uint32_t a, uint32_t& r0, uint32_t& r1, uint32_t& r2, uint32_t& r3) {
  asm volatile("ldmatrix.sync.aligned.m8n8.x4.shared.b16 {%0,%1,%2,%3}, [%4];" : "=r"(r0), "=r"(r1), "=r"(r2), "=r"(r3) : "r"(a) : "memory");
}
__device__ __forceinline__ void ldsm4t(uint32_t a, uint32_t& r0, uint32_t& r1, uint32_t& r2, uint32_t& r3) {
  asm volatile("ldmatrix.sync.aligned.m8n8.x4.trans.shared.b16 {%0,%1,%2,%3}, [%4];" : "=r"(r0), "=r"(r1), "=r"(r2), "=r"(r3) : "r"(a) : "memory");
}
__device__ __forceinline__ void stsm4(uint32_t a, uint32_t r0, uint32_t r1, uint32_t r2, uint32_t r3) {
  asm volatile("stmatrix.sync.aligned.m8n8.x4.shared.b16 [%0], {%1,%2,%3,%4};" ::"r"(a), "r"(r0), "r"(r1), "r"(r2), "r"(r3) : "memory");
}
__device__ __forceinline__ void mma16816(float (&c)[4], uint32_t a0, uint32_t a1, uint32_t a2, uint32_t a3, uint32_t b0, uint32_t b1) {
  asm volatile("mma.sync.aligned.m16n8k16.row.col.f32.bf16.bf16.f32 {%0,%1,%2,%3},{%4,%5,%6,%7},{%8,%9},{%0,%1,%2,%3};"
               : "+f"(c[0]), "+f"(c[1]), "+f"(c[2]), "+f"(c[3]) : "r"(a0), "r"(a1), "r"(a2), "r"(a3), "r"(b0), "r"(b1));
}
__device__ __forceinline__ uint32_t lds32(uint32_t a) { uint32_t v; asm volatile("ld.shared.b32 %0, [%1];" : "=r"(v) : "r"(a) : "memory"); return v; }
__device__ __forceinline__ float ldsf(uint32_t a) { float v; asm volatile("ld.shared.f32 %0, [%1];" : "=f"(v) : "r"(a) : "memory"); return v; }
__device__ __forceinline__ uint4 lds128(uint32_t a) {
  uint4 v; asm volatile("ld.shared.v4.b32 {%0,%1,%2,%3}, [%4];" : "=r"(v.x), "=r"(v.y), "=r"(v.z), "=r"(v.w) : "r"(a) : "memory"); return v;
}
__device__ __forceinline__ void sts16(uint32_t a, uint16_t v) { asm volatile("st.shared.b16 [%0], %1;" ::"r"(a), "h"(v) : "memory"); }
__device__ __forceinline__ void stsf(uint32_t a, float v) { asm volatile("st.shared.f32 [%0], %1;" ::"r"(a), "f"(v) : "memory"); }
__device__ __forceinline__ void sts64(uint32_t a, uint32_t x, uint32_t y) { asm volatile("st.shared.v2.b32 [%0], {%1,%2};" ::"r"(a), "r"(x), "r"(y) : "memory"); }
__device__ __forceinline__ void sts128(uint32_t a, uint32_t x, uint32_t y, uint32_t z, uint32_t w) {
  asm volatile("st.shared.v4.b32 [%0], {%1,%2,%3,%4};" ::"r"(a), "r"(x), "r"(y), "r"(z), "r"(w) : "memory");
}
__device__ __forceinline__ uint32_t pack2(float lo, float hi) { uint32_t r; asm("cvt.rn.bf16x2.f32 %0, %1, %2;" : "=r"(r) : "f"(hi), "f"(lo)); return r; }
__device__ __forceinline__ float blo(uint32_t v) { return __uint_as_float(v << 16); }
__device__ __forceinline__ float bhi(uint32_t v) { return __uint_as_float(v & 0xffff0000u); }
__device__ __forceinline__ float bfr(float v) { return __bfloat162float(__float2bfloat16_rn(v)); }
__device__ __forceinline__ uint32_t hsub2(uint32_t a, uint32_t b) { uint32_t r; asm("sub.rn.bf16x2 %0, %1, %2;" : "=r"(r) : "r"(a), "r"(b)); return r; }
__device__ __forceinline__ uint32_t hadd2(uint32_t a, uint32_t b) { uint32_t r; asm("add.rn.bf16x2 %0, %1, %2;" : "=r"(r) : "r"(a), "r"(b)); return r; }
__device__ __forceinline__ uint32_t hmul2(uint32_t a, uint32_t b) { uint32_t r; asm("mul.rn.bf16x2 %0, %1, %2;" : "=r"(r) : "r"(a), "r"(b)); return r; }
__device__ __forceinline__ uint32_t hfma2(uint32_t a, uint32_t b, uint32_t c) { uint32_t r; asm("fma.rn.bf16x2 %0, %1, %2, %3;" : "=r"(r) : "r"(a), "r"(b), "r"(c)); return r; }
__device__ __forceinline__ uint4 ld_relaxed16(const void* p) {
  unsigned long long a, b;
  asm volatile("ld.relaxed.gpu.global.v2.b64 {%0,%1}, [%2];" : "=l"(a), "=l"(b) : "l"(p) : "memory");
  return make_uint4((uint32_t)a, (uint32_t)(a >> 32), (uint32_t)b, (uint32_t)(b >> 32));
}
__device__ __forceinline__ uint4 ld_relaxed_b128(const void* p) {
  uint4 v;
  asm volatile("{.reg .b128 t; ld.relaxed.gpu.global.b128 t, [%4]; mov.b128 {%0,%1,%2,%3}, t;}" : "=r"(v.x), "=r"(v.y), "=r"(v.z), "=r"(v.w) : "l"(p) : "memory");
  return v;
}
__device__ __forceinline__ void st_relaxed_b128(void* p, uint32_t x, uint32_t y, uint32_t z, uint32_t w) {
  asm volatile("{.reg .b128 t; mov.b128 t, {%1,%2,%3,%4}; st.relaxed.gpu.global.b128 [%0], t;}" ::"l"(p), "r"(x), "r"(y), "r"(z), "r"(w) : "memory");
}
__device__ __forceinline__ void st_relaxed8(void* p, uint32_t x, uint32_t y) {
  unsigned long long v = ((unsigned long long)y << 32) | x;
  asm volatile("st.relaxed.gpu.global.b64 [%0], %1;" ::"l"(p), "l"(v) : "memory");
}
__device__ __forceinline__ void wg_fence() { asm volatile("wgmma.fence.sync.aligned;" ::: "memory"); }
__device__ __forceinline__ void wg_commit() { asm volatile("wgmma.commit_group.sync.aligned;" ::: "memory"); }
template <int N> __device__ __forceinline__ void wg_wait() { asm volatile("wgmma.wait_group.sync.aligned %0;" ::"n"(N) : "memory"); }
template <int N> __device__ __forceinline__ void reg_fence(float (&d)[N]) {
#pragma unroll
  for (int i = 0; i < N; i++) asm volatile("" : "+f"(d[i])::"memory");
}
#define DESC_HIWD (256u >> 4)
constexpr uint32_t DESC_HI128 = (1024u >> 4) | (1u << 30), DESC_HI64 = (512u >> 4) | (2u << 30);
template <uint32_t BHI, int SC> __device__ __forceinline__ void wgmma_ss_n128(float (&d)[64], uint32_t alo, uint32_t blo) {
  asm volatile("{.reg .b64 da, db; mov.b64 da, {%64, %66}; mov.b64 db, {%65, %67};\n"
    "wgmma.mma_async.sync.aligned.m64n128k16.f32.bf16.bf16 {%0,%1,%2,%3,%4,%5,%6,%7,%8,%9,%10,%11,%12,%13,%14,%15,%16,%17,%18,%19,%20,%21,%22,%23,%24,%25,%26,%27,%28,%29,%30,%31,%32,%33,%34,%35,%36,%37,%38,%39,%40,%41,%42,%43,%44,%45,%46,%47,%48,%49,%50,%51,%52,%53,%54,%55,%56,%57,%58,%59,%60,%61,%62,%63}, da, db, %68, 1, 1, 1, 1;}"
    : "+f"(d[0]),"+f"(d[1]),"+f"(d[2]),"+f"(d[3]),"+f"(d[4]),"+f"(d[5]),"+f"(d[6]),"+f"(d[7]),"+f"(d[8]),"+f"(d[9]),"+f"(d[10]),"+f"(d[11]),"+f"(d[12]),"+f"(d[13]),"+f"(d[14]),"+f"(d[15]),"+f"(d[16]),"+f"(d[17]),"+f"(d[18]),"+f"(d[19]),"+f"(d[20]),"+f"(d[21]),"+f"(d[22]),"+f"(d[23]),"+f"(d[24]),"+f"(d[25]),"+f"(d[26]),"+f"(d[27]),"+f"(d[28]),"+f"(d[29]),"+f"(d[30]),"+f"(d[31]),"+f"(d[32]),"+f"(d[33]),"+f"(d[34]),"+f"(d[35]),"+f"(d[36]),"+f"(d[37]),"+f"(d[38]),"+f"(d[39]),"+f"(d[40]),"+f"(d[41]),"+f"(d[42]),"+f"(d[43]),"+f"(d[44]),"+f"(d[45]),"+f"(d[46]),"+f"(d[47]),"+f"(d[48]),"+f"(d[49]),"+f"(d[50]),"+f"(d[51]),"+f"(d[52]),"+f"(d[53]),"+f"(d[54]),"+f"(d[55]),"+f"(d[56]),"+f"(d[57]),"+f"(d[58]),"+f"(d[59]),"+f"(d[60]),"+f"(d[61]),"+f"(d[62]),"+f"(d[63])
    : "r"(alo), "r"(blo), "n"(DESC_HI128), "n"(BHI), "n"(SC));
}
template <uint32_t BHI, int SC> __device__ __forceinline__ void wgmma_ss_n64(float (&d)[32], uint32_t alo, uint32_t blo) {
  asm volatile("{.reg .b64 da, db; mov.b64 da, {%32, %34}; mov.b64 db, {%33, %35};\n"
    "wgmma.mma_async.sync.aligned.m64n64k16.f32.bf16.bf16 {%0,%1,%2,%3,%4,%5,%6,%7,%8,%9,%10,%11,%12,%13,%14,%15,%16,%17,%18,%19,%20,%21,%22,%23,%24,%25,%26,%27,%28,%29,%30,%31}, da, db, %36, 1, 1, 1, 1;}"
    : "+f"(d[0]),"+f"(d[1]),"+f"(d[2]),"+f"(d[3]),"+f"(d[4]),"+f"(d[5]),"+f"(d[6]),"+f"(d[7]),"+f"(d[8]),"+f"(d[9]),"+f"(d[10]),"+f"(d[11]),"+f"(d[12]),"+f"(d[13]),"+f"(d[14]),"+f"(d[15]),"+f"(d[16]),"+f"(d[17]),"+f"(d[18]),"+f"(d[19]),"+f"(d[20]),"+f"(d[21]),"+f"(d[22]),"+f"(d[23]),"+f"(d[24]),"+f"(d[25]),"+f"(d[26]),"+f"(d[27]),"+f"(d[28]),"+f"(d[29]),"+f"(d[30]),"+f"(d[31])
    : "r"(alo), "r"(blo), "n"(DESC_HI128), "n"(BHI), "n"(SC));
}
template <int SC> __device__ __forceinline__ void wgmma_rs_n56(float (&d)[28], uint32_t a0, uint32_t a1, uint32_t a2, uint32_t a3, uint32_t blo) {
  asm volatile("{.reg .b64 db; mov.b64 db, {%32, %33};\n"
    "wgmma.mma_async.sync.aligned.m64n56k16.f32.bf16.bf16 {%0,%1,%2,%3,%4,%5,%6,%7,%8,%9,%10,%11,%12,%13,%14,%15,%16,%17,%18,%19,%20,%21,%22,%23,%24,%25,%26,%27}, {%28,%29,%30,%31}, db, %34, 1, 1, 1;}"
    : "+f"(d[0]),"+f"(d[1]),"+f"(d[2]),"+f"(d[3]),"+f"(d[4]),"+f"(d[5]),"+f"(d[6]),"+f"(d[7]),"+f"(d[8]),"+f"(d[9]),"+f"(d[10]),"+f"(d[11]),"+f"(d[12]),"+f"(d[13]),"+f"(d[14]),"+f"(d[15]),"+f"(d[16]),"+f"(d[17]),"+f"(d[18]),"+f"(d[19]),"+f"(d[20]),"+f"(d[21]),"+f"(d[22]),"+f"(d[23]),"+f"(d[24]),"+f"(d[25]),"+f"(d[26]),"+f"(d[27])
    : "r"(a0), "r"(a1), "r"(a2), "r"(a3), "r"(blo), "n"(DESC_HIWD), "n"(SC));
}
__device__ __forceinline__ void wgmma_aug_n128(float (&d)[64], uint32_t a0, uint32_t a1, uint32_t zero, uint32_t blo) {
  asm volatile("{.reg .b64 db; mov.b64 db, {%67, %68};\n"
    "wgmma.mma_async.sync.aligned.m64n128k16.f32.bf16.bf16 {%0,%1,%2,%3,%4,%5,%6,%7,%8,%9,%10,%11,%12,%13,%14,%15,%16,%17,%18,%19,%20,%21,%22,%23,%24,%25,%26,%27,%28,%29,%30,%31,%32,%33,%34,%35,%36,%37,%38,%39,%40,%41,%42,%43,%44,%45,%46,%47,%48,%49,%50,%51,%52,%53,%54,%55,%56,%57,%58,%59,%60,%61,%62,%63}, {%64,%65,%66,%66}, db, 1, 1, 1, 1;}"
    : "+f"(d[0]),"+f"(d[1]),"+f"(d[2]),"+f"(d[3]),"+f"(d[4]),"+f"(d[5]),"+f"(d[6]),"+f"(d[7]),"+f"(d[8]),"+f"(d[9]),"+f"(d[10]),"+f"(d[11]),"+f"(d[12]),"+f"(d[13]),"+f"(d[14]),"+f"(d[15]),"+f"(d[16]),"+f"(d[17]),"+f"(d[18]),"+f"(d[19]),"+f"(d[20]),"+f"(d[21]),"+f"(d[22]),"+f"(d[23]),"+f"(d[24]),"+f"(d[25]),"+f"(d[26]),"+f"(d[27]),"+f"(d[28]),"+f"(d[29]),"+f"(d[30]),"+f"(d[31]),"+f"(d[32]),"+f"(d[33]),"+f"(d[34]),"+f"(d[35]),"+f"(d[36]),"+f"(d[37]),"+f"(d[38]),"+f"(d[39]),"+f"(d[40]),"+f"(d[41]),"+f"(d[42]),"+f"(d[43]),"+f"(d[44]),"+f"(d[45]),"+f"(d[46]),"+f"(d[47]),"+f"(d[48]),"+f"(d[49]),"+f"(d[50]),"+f"(d[51]),"+f"(d[52]),"+f"(d[53]),"+f"(d[54]),"+f"(d[55]),"+f"(d[56]),"+f"(d[57]),"+f"(d[58]),"+f"(d[59]),"+f"(d[60]),"+f"(d[61]),"+f"(d[62]),"+f"(d[63])
    : "r"(a0), "r"(a1), "r"(zero), "r"(blo), "n"(1u << 30));
}
__device__ __forceinline__ void wgmma_aug_n64(float (&d)[32], uint32_t a0, uint32_t a1, uint32_t zero, uint32_t blo) {
  asm volatile("{.reg .b64 db; mov.b64 db, {%35, %36};\n"
    "wgmma.mma_async.sync.aligned.m64n64k16.f32.bf16.bf16 {%0,%1,%2,%3,%4,%5,%6,%7,%8,%9,%10,%11,%12,%13,%14,%15,%16,%17,%18,%19,%20,%21,%22,%23,%24,%25,%26,%27,%28,%29,%30,%31}, {%32,%33,%34,%34}, db, 1, 1, 1, 1;}"
    : "+f"(d[0]),"+f"(d[1]),"+f"(d[2]),"+f"(d[3]),"+f"(d[4]),"+f"(d[5]),"+f"(d[6]),"+f"(d[7]),"+f"(d[8]),"+f"(d[9]),"+f"(d[10]),"+f"(d[11]),"+f"(d[12]),"+f"(d[13]),"+f"(d[14]),"+f"(d[15]),"+f"(d[16]),"+f"(d[17]),"+f"(d[18]),"+f"(d[19]),"+f"(d[20]),"+f"(d[21]),"+f"(d[22]),"+f"(d[23]),"+f"(d[24]),"+f"(d[25]),"+f"(d[26]),"+f"(d[27]),"+f"(d[28]),"+f"(d[29]),"+f"(d[30]),"+f"(d[31])
    : "r"(a0), "r"(a1), "r"(zero), "r"(blo), "n"(1u << 30));
}

struct Params {
  const __nv_bfloat16 *x, *Are, *Aim, *Bre, *Bim, *Cre, *Cim, *logdt, *dskip;
  Scratch* s;
  const uint32_t* lut;
  __nv_bfloat16* out;
  const __nv_bfloat16* wd;
  uint32_t zero;
};

struct cf { float r, i; };
__device__ __forceinline__ cf cmul(cf a, cf b) { cf c; c.r = fmaf(a.r, b.r, -a.i * b.i); c.i = fmaf(a.r, b.i, a.i * b.r); return c; }
__device__ __forceinline__ cf cexp_e(float a2, float th, float tl, float e) {
  float t = th * e;
  float r = (t - rintf(t)) + tl * e;
  float ang = r * 6.283185307179586f;
  float mag;
  asm("ex2.approx.ftz.f32 %0, %1;" : "=f"(mag) : "f"(a2 * e));
  cf z; z.r = mag * __cosf(ang); z.i = mag * __sinf(ang);
  return z;
}

template <int FAR, int TAB, int S0, int NS0, int GRP>
__device__ __forceinline__ void far_seq(float (&acc)[4][4], uint32_t fb, uint32_t gf, uint32_t z) {
  constexpr int NS = S0 + NS0 - 1 > 4 * GRP + 3 ? 4 * GRP + 4 - S0 : NS0;
  constexpr int RHI = 3 - S0, RL0 = -(S0 + NS - 1) < -4 * GRP ? -4 * GRP : -(S0 + NS - 1);
  constexpr int NB = (RHI - RL0 + 2) / 2 * 2, RLO = RHI - NB + 1;
  uint32_t H[NB][2], G[2 * NS + 1];
#pragma unroll
  for (int q = NB / 2 - 1; q >= 0; q--)
    ldsm4t(fb + (FAR + 16 * (RLO + 2 * q)) * 16, H[2 * q][0], H[2 * q][1], H[2 * q + 1][0], H[2 * q + 1][1]);
#pragma unroll
  for (int k = 0; k < 2 * NS + 1; k++) G[k] = lds32(gf + TAB * 2 + k * 16);
#pragma unroll
  for (int j = 0; j < NS; j++) {
    const uint32_t a0 = j ? G[2 * j] + z : G[0], a2 = G[2 * j + 1] + z;
#pragma unroll
    for (int i = 3; i >= 0; i--) {
      const int r = i - S0 - j;
      if (r >= RL0) mma16816(acc[i], a0, G[2 * j + 1], a2, G[2 * j + 2], H[r - RLO][0], H[r - RLO][1]);
    }
  }
}
template <int GRP> __device__ __forceinline__ void far_mid(float (&acc)[4][4], uint32_t fb, uint32_t gf, uint32_t z) {
  far_seq<FAR_B30, T_B30, 2, 3, GRP>(acc, fb, gf, z);
  far_seq<FAR_U2, T_U2, 2, 3, GRP>(acc, fb, gf, z);
  far_seq<FAR_U6, T_U6, 2, 3, GRP>(acc, fb, gf, z);
  far_seq<FAR_B34, T_B34, 2, 7, GRP>(acc, fb, gf, z);
  if (GRP >= 1) far_seq<FAR_B5, T_B5, 4, 5, GRP ? GRP : 1>(acc, fb, gf, z);
}
template <int GRP> __device__ __forceinline__ void far_far(float (&acc)[4][4], uint32_t fb, uint32_t gf, uint32_t z) {
  far_seq<FAR_B7, T_B7, 8, 8, GRP>(acc, fb, gf, z);
  far_seq<FAR_U5, T_U5, 8, 1, GRP>(acc, fb, gf, z);
  far_seq<FAR_B9, T_B9, 8, 8, GRP>(acc, fb, gf, z);
}

__device__ __forceinline__ void step2_item(uint32_t sb, int wi, int lane) {
  const int it2 = wi >> 2, ch = wi & 3;
  const int c = 32 * it2 + lane - 1;
  const uint32_t ua = sb + SM_U + ch * U_CH + (U_PAD + c) * 16;
  uint2 pv;
  asm volatile("ld.shared.v2.b32 {%0,%1}, [%2];" : "=r"(pv.x), "=r"(pv.y) : "r"(ua - 8) : "memory");
  const uint4 cu = lds128(ua), nx = lds128(ua + 16);
  const uint32_t fa = sb + SM_FAR + ch * STAGE + (c + 1) * 16;
  sts128(fa + FAR_U2 * 16, cu.w, nx.x, nx.y, nx.z);
  sts128(fa + FAR_U6 * 16, cu.y, cu.z, cu.w, nx.x);
  const uint32_t e[8] = {pv.x, pv.y, cu.x, cu.y, cu.z, cu.w, nx.x, nx.y};
  uint32_t o[7], r[4];
#pragma unroll
  for (int k = 0; k < 7; k++) o[k] = __byte_perm(e[k], e[k + 1], 0x5432);
#pragma unroll
  for (int k = 0; k < 4; k++) r[k] = hadd2(e[k + 2], hadd2(o[k + 1], o[k + 2]));
  sts128(fa + FAR_B30 * 16, r[0], r[1], r[2], r[3]);
  sts64(fa + FAR_B34 * 16 - 8, r[0], r[1]);
  sts64(fa + FAR_B34 * 16, r[2], r[3]);
  if (it2 < 6) {
#pragma unroll
    for (int k = 0; k < 4; k++) r[k] = hadd2(r[k], hadd2(e[k + 1], e[k + 3]));
    sts128(fa + FAR_B5 * 16, r[0], r[1], r[2], r[3]);
  } else if (lane == 31) {
    sts64(fa + FAR_B34 * 16 + 8, 0, 0);
    sts128(sb + SM_FAR + ch * STAGE + FAR_B9 * 16, 0, 0, 0, 0);
  }
  if (it2 < 4) {
#pragma unroll
    for (int k = 0; k < 4; k++) r[k] = hadd2(r[k], hadd2(o[k], o[k + 3]));
    sts128(fa + FAR_B7 * 16, r[0], r[1], r[2], r[3]);
#pragma unroll
    for (int k = 0; k < 4; k++) r[k] = hadd2(r[k], hadd2(e[k], e[k + 4]));
    sts128(fa + FAR_B9 * 16 + 16, r[0], r[1], r[2], r[3]);
    sts128(fa + FAR_U5 * 16, o[3], o[4], o[5], o[6]);
  }
}

__device__ __forceinline__ void build_tables(uint32_t sb, const uint32_t (&lut)[6], int wg, int c) {
#pragma unroll
  for (int r = 0; r < 6; r++) {
    const uint32_t e = lut[r];
    if (r < 5 || e != 0xffffffffu) {
      {
        const uint32_t src = sb + SM_STG + wg * STAGE + (c ? 4096 : 1152) + (e & 1023) * 4, dst = sb + SM_TAB + (wg + 2 * c) * STAGE + ((e >> 10) & 1023) * 2;
        const float vv = (ldsf(src) + ldsf(src + 7168)) + (ldsf(src + 2 * 7168) + ldsf(src + 3 * 7168));
        const uint16_t h = (uint16_t)(pack2(vv, 0.f) ^ ((e >> 5) & 0x8000u));
        sts16(dst, h); sts16(dst + TAB_ODD - 2, h);
      }
    }
  }
}

__global__ void __cluster_dims__(2, 1, 1) __launch_bounds__(NTHR, 1)
fused_kernel(const Params p,
             const __grid_constant__ CUtensorMap tm_wg128, const __grid_constant__ CUtensorMap tm_wu128,
             const __grid_constant__ CUtensorMap tm_wg64, const __grid_constant__ CUtensorMap tm_wu64,
             const __grid_constant__ CUtensorMap tm_wd, const __grid_constant__ CUtensorMap tm_h) {
  extern __shared__ __align__(1024) unsigned char smem[];
  const uint32_t sb = smem_u32(smem);
  const int tid = threadIdx.x, lane = tid & 31;
  const uint32_t b = blockIdx.x;
  const bool conv_cta = b < NCONV;
  if ((sb & 0x3ffff) != SMEM_BASE) return;
  const uint32_t bar = sb + SM_BAR;
  uint4 v[7];
  uint32_t lut[6], sraw;
  const size_t po = (size_t)b * 512 + 2 * tid;
  if (tid >= 256) {
    const uint4* src = (const uint4*)(p.x + (size_t)(16 * b + ((tid - 256) >> 3)) * D_) + (lane & 7);
#pragma unroll
    for (int i = 0; i < 7; i++)
      asm volatile("ld.global.nc.v4.u32 {%0,%1,%2,%3}, [%4];" : "=r"(v[i].x), "=r"(v[i].y), "=r"(v[i].z), "=r"(v[i].w) : "l"(src + 8 * i));
  } else if (conv_cta) {
    asm volatile("ld.global.nc.u32 %0, [%1];" : "=r"(v[0].x) : "l"(p.Are + po));
    asm volatile("ld.global.nc.u32 %0, [%1];" : "=r"(v[0].y) : "l"(p.Aim + po));
    asm volatile("ld.global.nc.u32 %0, [%1];" : "=r"(sraw) : "l"(p.logdt + 2 * b));
    asm volatile("ld.global.nc.u32 %0, [%1];" : "=r"(v[0].z) : "l"(p.Bre + po));
    asm volatile("ld.global.nc.u32 %0, [%1];" : "=r"(v[0].w) : "l"(p.Bim + po));
    asm volatile("ld.global.nc.u32 %0, [%1];" : "=r"(v[1].x) : "l"(p.Cre + po));
    asm volatile("ld.global.nc.u32 %0, [%1];" : "=r"(v[1].y) : "l"(p.Cim + po));
  }
  uint32_t eraw;
  asm volatile("ld.relaxed.gpu.global.u32 %0, [%1];" : "=r"(eraw) : "l"(&p.s->epoch[b]));
#define EPOCH (eraw + 1)
#define TAG ((eraw + 1) & 0xffffu)
  const int warp = __shfl_sync(~0u, tid >> 5, 0);
  const int g = lane >> 2, t = lane & 3;

  if (warp >= 8) {
    {
      const int t2 = tid - 256, iw = warp - 8;
      const uint32_t trb = sb + (conv_cta ? SM_TRC : SM_TRS);
      const uint32_t ta = trb + (t2 >> 3) * TR_PITCH + (t2 >> 6) * 16 + (lane & 7) * 16;
      const int rr = 8 * ((lane >> 1) & 1) + 2 * (lane >> 3) + (lane & 1);
      const uint32_t la = trb + rr * TR_PITCH + (rr >> 3) * 16 + ((lane >> 2) & 1) * 448 + iw * 16;
      uint4* dst = p.s->ux + ((size_t)(4 * iw + (g >> 1)) * 128 + b) * 16 + (t >> 1) * 4 + (g & 1) * 2 + (t & 1);
      if (conv_cta) {
        sts128(sb + SM_U + iw * U_CH + lane * 16, 0, 0, 0, 0);
        if (lane < U_PAD - 32) sts128(sb + SM_U + iw * U_CH + (32 + lane) * 16, 0, 0, 0, 0);
      }
      {
        float sa[4] = {0.f, 0.f, 0.f, 0.f}, q1[4] = {0.f, 0.f, 0.f, 0.f}, q2[4] = {0.f, 0.f, 0.f, 0.f};
#pragma unroll
        for (int i = 0; i < 7; i++) {
          mma16816(sa, v[i].x, v[i].y, v[i].z, v[i].w, 0x3f803f80u, 0x3f803f80u);
          mma16816(q1, v[i].x, v[i].z, v[i].y, v[i].w, v[i].x, v[i].y);
          mma16816(q2, v[i].x, v[i].z, v[i].y, v[i].w, v[i].z, v[i].w);
        }
        float s = sa[0] + sa[2];
        float qq = (g & 1) ? q1[1] + q2[3] : q1[0] + q2[2];
        qq = __shfl_sync(~0u, qq, (lane & ~3) | (g >> 1));
        s += __shfl_xor_sync(~0u, s, 4);
        qq += __shfl_xor_sync(~0u, qq, 4);
        const float mean = s * (1.f / D_);
        const float var = fmaxf(fmaf(-mean, mean, qq * (1.f / D_)), 0.f);
        const float sd = bfr(__fsqrt_rn(bfr(bfr(var) + 1e-5f)));
        const float rs = __frcp_rn(sd), rh = bfr(rs);
        const uint32_t m2 = pack2(mean, mean), rh2 = pack2(rh, rh), rl2 = pack2(rs - rh, rs - rh);
        uint32_t w[28];
#pragma unroll
        for (int i = 0; i < 7; i++) { w[4 * i] = v[i].x; w[4 * i + 1] = v[i].y; w[4 * i + 2] = v[i].z; w[4 * i + 3] = v[i].w; }
#pragma unroll
        for (int i = 0; i < 28; i++) { const uint32_t d0 = hsub2(w[i], m2); w[i] = hfma2(d0, rh2, hmul2(d0, rl2)); }
#pragma unroll
        for (int i = 0; i < 7; i++) sts128(ta + i * 128, w[4 * i], w[4 * i + 1], w[4 * i + 2], w[4 * i + 3]);
        asm volatile("bar.sync 1, 128;" ::: "memory");
#pragma unroll
        for (int i = 0; i < 7; i++) ldsm4t(la + i * 64, w[4 * i], w[4 * i + 1], w[4 * i + 2], w[4 * i + 3]);
#pragma unroll
        for (int i = 0; i < 7; i++) st_relaxed_b128(dst + (size_t)i * (16 * 128 * 16), w[4 * i], w[4 * i + 1], w[4 * i + 2], ~w[4 * i + 3]);
        asm volatile("bar.arrive 4, 384;" ::: "memory");
        asm volatile("bar.sync 1, 128;" ::: "memory");
        if (t2 == 0) asm volatile("red.relaxed.gpu.global.add.u32 [%0], 1;" ::"l"(&p.s->cnt[160]) : "memory");
      }
#pragma unroll
      for (int i = 0; i < 7; i++) sts128(ta + i * 128, v[i].x, v[i].y, v[i].z, v[i].w);
      if (t2 == 0) {
        uint32_t hv, it = 0;
        do { asm volatile("ld.relaxed.gpu.global.u32 %0, [%1];" : "=r"(hv) : "l"(&p.s->cnt[160]) : "memory"); SPIN_CHECK(it); } while ((int)(hv - EPOCH * NCTA) < 0);
      }
      asm volatile("bar.sync 0, 256;" ::: "memory");
      asm volatile("barrier.cluster.arrive.relaxed.aligned;" ::: "memory");
      const uint4* src2 = p.s->ux + (size_t)b * 2048 + (t2 >> 3) * 16 + (t2 & 7);
      uint32_t da = sb + SM_U + ((t2 >> 1) & 3) * U_CH + (U_PAD + 2 * (t2 >> 3) + (t2 & 1)) * 16;
#pragma unroll 1
      for (int a2 = 0; a2 < 2; a2++) {
        uint32_t it = 0;
        uint4 sv[8];
        bool ok;
        const bool rcv = conv_cta;
        do {
          ok = true;
          if (rcv) {
#pragma unroll
            for (int i = 0; i < 8; i++) sv[i] = ld_relaxed_b128(src2 + i * 256);
          }
          if (a2 == 0 && it == 0) {
#pragma unroll
            for (int i = 0; i < 7; i++) ldsm4t(la + i * 64, v[i].x, v[i].y, v[i].z, v[i].w);
          }
          if (!rcv) break;
#pragma unroll
          for (int i = 0; i < 8; i++) ok = ok && sv[i].w != 0;
          SPIN_CHECK(it);
        } while (!ok);
        if (rcv) {
#pragma unroll
          for (int i = 0; i < 8; i++) sts128(da + i * 512, sv[i].x, sv[i].y, sv[i].z, ~sv[i].w);
        }
        if (a2 == 0) {
          if (rcv) asm volatile("bar.arrive 7, 256;" ::: "memory");
#pragma unroll
          for (int i = 0; i < 7; i++) st_relaxed_b128(dst + (size_t)i * (16 * 128 * 16) + 8, v[i].x, v[i].y, v[i].z, max(~v[i].w, 1u));
          if (t2 == 64) asm volatile("cp.async.bulk.prefetch.L2.global [%0], %1;" ::"l"((const char*)p.wd + (size_t)b * 12544), "r"(12544) : "memory");
          if (!rcv) break;
          src2 += 8;
          da = sb + SM_X + ((t2 >> 1) & 3) * X_CH + (2 * (t2 >> 3) + (t2 & 1)) * 16;
        } else {
          __syncwarp();
          if (lane == 0) mbar_arrive(bar + 8 * B_XT);
        }
        if (a2 == 0) asm volatile("bar.sync 1, 128;" ::: "memory");
#pragma unroll 1
        for (int k = a2 ? iw >> 1 : iw; k < 7; k += a2 ? 2 : 4) step2_item(sb, 4 * k + (a2 ? 2 + (iw & 1) : 0), lane);
        if (a2 == 0) { asm volatile("bar.arrive 6, 256;" ::: "memory"); }
      }
      asm volatile("fence.proxy.async.shared::cta;" ::: "memory");
      if (conv_cta) { asm volatile("bar.arrive 4, 256;" ::: "memory"); asm volatile("bar.arrive 5, 256;" ::: "memory"); }
    }
    asm volatile("setmaxnreg.dec.sync.aligned.u32 40;");
    FRESH_IDS
    if (!conv_cta) asm volatile("bar.sync 8, 384;" ::: "memory");
    else if (warp == 8) { asm volatile("bar.sync 0, 288;" ::: "memory"); asm volatile("fence.proxy.async.shared::cta;" ::: "memory"); }
    if (warp == 8) {
      const int i = lane;
      const uint32_t e = i < 2 ? (24u | i) : (uint32_t)((i < 12 ? ST_P0 : ST_P1) >> ((6 * (i < 12 ? i - 2 : i - 12)) & 63));
      const uint32_t slot = e & 7, dsl = (e >> 3) & 3;
      const uint32_t dst = sb + (slot < 4 ? SM_RING + slot * STAGE : SM_A + (slot - 4) * STAGE), fb = bar + 8 * (B_FULL + slot);
      const bool n64 = i == 7 || i == 1;
      const int col = 224 * f + (n64 ? 192 * (ra ^ 1) : 32 * ra + 64 * ((0xaa50140u >> ((2 * i) & 31)) & 3));
      const int q = (0xe4eb910u >> ((2 * i) & 31)) & 3;
      const int k = i - 14;
      const int half = k < 4 ? (k >> 1) : (k & 1), xm = k < 4 ? (2 | (k & 1)) : (k < 6 ? 1 : 0);
      const uint4* s0 = p.s->wdp + ((4 * ra + (sp ^ xm)) * 16 + half + 2 * f) * 784;
      const CUtensorMap* mg = n64 ? &tm_wg64 : &tm_wg128;
#pragma unroll 1
      for (int st = 0; st < 22; st++) {
        if (st == 12) {
          mbar_wait(bar + 8 * B_WD3, 0);
          asm volatile("fence.proxy.async.global;" ::: "memory");
        }
        if (lane == st) {
          if (st == 2 && conv_cta) mbar_wait(bar + 8 * B_XT2, 0);
          if (st == 3) mbar_wait(bar + 8 * B_WD2, 0);
          if (dsl < 3) mbar_wait(bar + 8 * (B_EMPTY + dsl), (e >> 5) & 1);
          mbar_expect(fb, st < 14 ? STAGE : 25088);
          if (st < 14) {
            tma2d(dst, mg, col, 112 * q, fb);
            tma2d(dst + 14336, mg + 1, col, 112 * q, fb);
          } else {
            bulk_ld(dst, s0, 12544, fb);
            bulk_ld(dst + 12544, s0 + (ra ? -2 * 784 : 2 * 784), 12544, fb);
          }
        }
        __syncwarp();
      }
    } else if (warp == 9) {
      if (lane == 0) {
#pragma unroll 1
        for (int c = 0; c < 2; c++) {
          {
            if (conv_cta) {
              mbar_wait(bar + 8 * (B_CH + c), 0);
              bulk_st(p.s->hT + (size_t)(224 * c + 2 * b) * L_, sb + SM_X + 2 * c * X_CH, 4096);
              bulk_st(p.s->hT + (size_t)(224 * c + 2 * b + 1) * L_, sb + SM_X + (2 * c + 1) * X_CH, 4096);
              asm volatile("cp.async.bulk.commit_group;" ::: "memory");
              if (c) { asm volatile("cp.async.bulk.wait_group.read 0;" ::: "memory"); mbar_arrive(bar + 8 * B_XT2); }
              asm volatile("cp.async.bulk.wait_group 0;" ::: "memory");
            }
            asm volatile("red.relaxed.gpu.global.add.u32 [%0], 1;" ::"l"(&p.s->cnt[32 * c]) : "memory");
          }
          if (c == 0) mbar_arrive(bar + 8 * B_X);
          uint32_t cv, it = 0;
          do { asm volatile("ld.acquire.gpu.global.u32 %0, [%1];" : "=r"(cv) : "l"(&p.s->cnt[32 * c]) : "memory"); SPIN_CHECK(it); } while ((int)(cv - EPOCH * NCTA) < 0);
          asm volatile("fence.proxy.async.global;" ::: "memory");
#pragma unroll 1
          for (int q = 2 * c; q < 2 * c + 2; q++) {
            const uint32_t ab = bar + 8 * (B_AFULL + q);
            mbar_expect(ab, STAGE);
            tma2d_mc(sb + SM_A + q * STAGE + ra * 14336, &tm_h, 128 * rt + 64 * ra, 112 * q, ab);
          }
        }
      }
      if (lane == 0) {
        uint32_t cv, it = 0;
        do { asm volatile("ld.acquire.gpu.global.u32 %0, [%1];" : "=r"(cv) : "l"(&p.s->cnt[128]) : "memory"); SPIN_CHECK(it); } while ((int)(cv - EPOCH * NCTA) < 0);
        mbar_arrive(bar + 8 * B_WD3);
      }
      __syncwarp();
      if (conv_cta) {
        uint4* z = p.s->ux + (size_t)b * 2048 + lane;
#pragma unroll 1
        for (int i = 0; i < 64; i++) { z[i * 32] = make_uint4(0, 0, 0, 0); __nanosleep(20); }
      }
    } else {
      const int ww = warp - 10;
      if (ww == 1) {
        if (lane == 0) {
          const int fs = (b >> 1) & 7;
          mbar_expect(bar + 8 * B_WD, 12544);
#pragma unroll 1
          for (int i = 0; i < 7; i++) {
            int lr = 112 * (b & 1) + 16 * i + 192 * ((fs & 1) ^ 1);
            if (lr >= 224) lr -= 224;
            tma3d(sb + SM_WDI + i * 1792, &tm_wd, 0, 224 * fs + lr, 7 * (b >> 4), bar + 8 * B_WD);
          }
        }
        __syncwarp();
        sts64(sb + SM_CS + 1024 + 768 + lane * 8, 0, 0);
#pragma unroll 1
        for (int k = 0; k < 4; k++) if (lane < 28) {
          const uint2* src = &p.s->cs[224 * f + 2 * lane + 56 * k];
          uint4 cv[2]; uint32_t it = 0;
          do { cv[0] = ld_relaxed16(src); cv[1] = ld_relaxed16(src + F_); SPIN_CHECK(it);
          } while (cv[0].y != EPOCH || cv[0].w != EPOCH || cv[1].y != EPOCH || cv[1].w != EPOCH);
          int pr = lane + 28 * k + 16 * (ra ^ 1);
          if (pr >= 112) pr -= 112;
#pragma unroll
          for (int m = 0; m < 2; m++) {
            const int job = pr < 16 ? 3 : (pr - 16) >> 5, cp = pr < 16 ? pr + 16 * m : (pr - 16) & 31;
            const uint32_t ab = sb + SM_CS + (pr < 16 ? 0 : m * 1024) + job * 256 + (cp & 3) * 4;
            const float c0 = __uint_as_float(cv[m].x), c1 = __uint_as_float(cv[m].z);
            const uint32_t hi = pack2(c0, c1), lo = pack2(c0 - blo(hi), c1 - bhi(hi));
            stsf(ab + (((cp >> 2) ^ (2 * job)) * 16), __uint_as_float(hi));
            stsf(ab + 128 + (((cp >> 2) ^ (2 * job + 1)) * 16), __uint_as_float(lo));
          }
        }
        asm volatile("fence.proxy.async.shared::cta;" ::: "memory");
        __syncwarp();
        if (lane == 0) {
          mbar_arrive(bar + 8 * B_AUX);
          mbar_wait(bar + 8 * B_X, conv_cta ? 0 : 1);
          mbar_wait(bar + 8 * B_WD, 0);
          bulk_st(p.s->wdp + b * 784, sb + SM_WDI, 12544);
          asm volatile("cp.async.bulk.commit_group;" ::: "memory");
          asm volatile("cp.async.bulk.wait_group.read 0;" ::: "memory");
          mbar_arrive(bar + 8 * B_WD2);
          asm volatile("cp.async.bulk.wait_group 0;" ::: "memory");
          asm volatile("red.relaxed.gpu.global.add.u32 [%0], 1;" ::"l"(&p.s->cnt[128]) : "memory");
        }
      }
      __syncwarp();
      const uint32_t aa = sb + SM_A + ww * STAGE + (f >> 2) * 14336 + ((lane >> 4) * 8 + (lane & 7)) * 128 + (((2 * (f & 3) + ((lane >> 3) & 1)) ^ (lane & 7)) * 16);
      float s0 = 0.f, s1 = 0.f, q0 = 0.f, q1 = 0.f;
#pragma unroll 1
      for (int q2 = 0; q2 < 2; q2++) {
        mbar_wait(bar + 8 * (B_AFULL + ww + 2 * q2), 0);
        uint32_t fr[7][4];
#pragma unroll
        for (int j = 0; j < 7; j++) ldsm4t(aa + q2 * (2 * STAGE) + j * 2048, fr[j][0], fr[j][1], fr[j][2], fr[j][3]);
#pragma unroll
        for (int j = 0; j < 7; j++) {
          const uint32_t (&r)[4] = fr[j];
#pragma unroll
          for (int k = 0; k < 4; k += 2) {
            const float a = blo(r[k]), c = bhi(r[k]), d = blo(r[k + 1]), e = bhi(r[k + 1]);
            s0 += a + c; q0 = fmaf(a, a, fmaf(c, c, q0));
            s1 += d + e; q1 = fmaf(d, d, fmaf(e, e, q1));
          }
        }
      }
      { const bool o = lane & 1;
        s0 = (o ? s1 : s0) + __shfl_xor_sync(~0u, o ? s0 : s1, 1);
        q0 = (o ? q1 : q0) + __shfl_xor_sync(~0u, o ? q0 : q1, 1);
        const bool h = lane & 2;
        s0 = (h ? q0 : s0) + __shfl_xor_sync(~0u, h ? s0 : q0, 2); }
      const uint32_t tag = TAG;
      if (ww == 1) { stsf(sb + SM_RED + lane * 4, s0); asm volatile("bar.arrive 1, 64;" ::: "memory"); }
      else {
        asm volatile("bar.sync 1, 64;" ::: "memory");
        const float s = s0 + ldsf(sb + SM_RED + lane * 4);
        const float q = __shfl_down_sync(~0u, s, 2);
        const float mean = s * (1.f / D_);
        const float var = fmaxf(q * (1.f / D_) - mean * mean, 0.f);
        const float sd = bfr(__fsqrt_rn(bfr(bfr(var) + 1e-5f)));
        const float rs = __frcp_rn(sd);
        const int row = 128 * rt + 16 * f + 8 * (lane & 1) + (lane >> 2);
        if ((lane & 2) == 0) st_relaxed8(&p.s->st2[row], __float_as_uint(rs * rs), (pack2(mean, 0.f) & 0xffffu) | (tag << 16));
        if (lane == 0) p.s->epoch[b] = EPOCH;
      }
      if (ww == 1) {
        uint4 c0, c1; uint32_t it = 0;
        do { c0 = ld_relaxed16(&p.s->st2[128 * rt + 4 * lane]); c1 = ld_relaxed16(&p.s->st2[128 * rt + 4 * lane + 2]); SPIN_CHECK(it);
        } while ((c0.y >> 16) != tag || (c0.w >> 16) != tag || (c1.y >> 16) != tag || (c1.w >> 16) != tag);
        sts64(sb + SM_M2 + lane * 8, __byte_perm(c0.y, c0.w, 0x5410) ^ 0x80008000u, __byte_perm(c1.y, c1.w, 0x5410) ^ 0x80008000u);
        sts128(sb + SM_RS2 + lane * 16, c0.x, c0.z, c1.x, c1.z);
        __syncwarp();
        if (lane == 0) mbar_arrive(bar + 8 * B_AUX);
      }
    }
  } else {
    if (warp < 4) {
      if (lane == 0) {
#pragma unroll 1
        for (int i = warp; i <= B_X; i += 4) {
          mbar_init(bar + 8 * i, i < B_FULL ? 8 : (i == B_AUX ? 2 : (i == B_XT ? 4 : 1)));
          if (i == B_MBF0 || i == B_MBF1) mbar_expect(bar + 8 * i, i == B_MBF0 ? 16384 : 8192);
        }
        asm volatile("fence.mbarrier_init.release.cluster;" ::: "memory");
      }
      __syncwarp();
      asm volatile("bar.arrive 0, 256;" ::: "memory");
    }
    asm volatile("barrier.cluster.arrive.relaxed.aligned;" ::: "memory");
    if (conv_cta) {
      const int wg = warp >> 2, wt = tid & 127;
#pragma unroll 1
      for (int i = wt; i < 264; i += 128) { sts128(sb + SM_TAB + wg * STAGE + 16 * i, 0, 0, 0, 0); sts128(sb + SM_TAB + (2 + wg) * STAGE + 16 * i, 0, 0, 0, 0); }
      const uint32_t stg = sb + SM_STG + warp * 7168;
      const uint32_t st_a = stg + lane * 16;
      const uint32_t ld_c = stg + 4096 + ((lane >> 3) & 1) * 512 + (lane >> 4) * 128 + (lane & 7) * 16;
      const uint32_t g_near = sb + SM_TAB + (T_F0 + 272 - g + 2 * t) * 2 + ((g & 1) ? TAB_ODD - 2 : 0);
      const uint32_t g_far0 = sb + SM_TAB + (1 + g + 2 * t) * 2 + ((g & 1) ? 0 : TAB_ODD - 2);
      const uint32_t z = p.zero;
      if (wg == 0) asm volatile("bar.sync 4, 384;" ::: "memory");
      else asm volatile("bar.arrive 4, 384;" ::: "memory");
      uint2 dskraw;
      asm volatile("ld.global.nc.u32 %0, [%1];" : "=r"(dskraw.x) : "l"(p.dskip + 2 * b + (lane & z)));
      asm volatile("ld.global.nc.u32 %0, [%1];" : "=r"(dskraw.y) : "l"(p.dskip + 224 + 2 * b + (lane & z)));
#pragma unroll
      for (int i = 0; i < 6; i++) asm volatile("ld.global.nc.u32 %0, [%1];" : "=r"(lut[i]) : "l"(p.lut + wt + 128 * i));
#pragma unroll 1
      for (int ph = 0; ph < 4; ph++) {
        if (ph < 2) {
          float kacc[2][3][4];
#pragma unroll
          for (int i = 0; i < 24; i++) (&kacc[0][0][0])[i] = 0.f;
          const float dt = bfr(expf(__uint_as_float(__byte_perm(sraw, 0, warp < 4 ? 0x1044u : 0x3244u))));
          const uint32_t w0 = v[0].x, w1 = v[0].y, w2 = v[0].z, w3 = v[0].w, w4 = v[1].x, w5 = v[1].y;
          if (ph == 0) {
            asm volatile("ld.global.nc.u32 %0, [%1];" : "=r"(v[0].x) : "l"(p.Are + po + 224 * NM + (w0 & z)));
            asm volatile("ld.global.nc.u32 %0, [%1];" : "=r"(v[0].y) : "l"(p.Aim + po + 224 * NM));
            asm volatile("ld.global.nc.u32 %0, [%1];" : "=r"(v[0].z) : "l"(p.Bre + po + 224 * NM));
            asm volatile("ld.global.nc.u32 %0, [%1];" : "=r"(v[0].w) : "l"(p.Bim + po + 224 * NM));
            asm volatile("ld.global.nc.u32 %0, [%1];" : "=r"(v[1].x) : "l"(p.Cre + po + 224 * NM));
            asm volatile("ld.global.nc.u32 %0, [%1];" : "=r"(v[1].y) : "l"(p.Cim + po + 224 * NM));
            asm volatile("ld.global.nc.u32 %0, [%1];" : "=r"(sraw) : "l"(p.logdt + 224 + 2 * b + (lane & z)));
          }
#pragma unroll
          for (int u = 0; u < 2; u++) {
          const float are = u ? bhi(w0) : blo(w0), aim = u ? bhi(w1) : blo(w1), bre = u ? bhi(w2) : blo(w2);
          const float bim = u ? bhi(w3) : blo(w3), cre = u ? bhi(w4) : blo(w4), cim = u ? bhi(w5) : blo(w5);
          const float a2 = (dt * are) * 1.4426950408889634f;
          const float bb = dt * aim;
          const float th = bb * 0.15915494309189535f;
          const float tl = fmaf(bb, 0.15915494309189535f, -th) + bb * 6.4206383e-9f;
          const cf z8 = cexp_e(a2, th, tl, 8.f);
          cf z1 = cexp_e(a2, th, tl, 1.f), z256 = cexp_e(a2, th, tl, 256.f);
          z1.i = -z1.i; z256.i = -z256.i;
          cf w; { cf c = {cre, cim}, db = {dt * bre, dt * bim}; w = cmul(c, db); w.i = -w.i; }
          const cf q2 = cmul(z8, z8), q3 = cmul(q2, z8), q4 = cmul(q2, q2), q5 = cmul(q4, z8), q6 = cmul(q4, q2), q7 = cmul(q4, q3);
          const uint32_t R[4] = {pack2(1.f, z8.r), pack2(q2.r, q3.r), pack2(q4.r, q5.r), pack2(q6.r, q7.r)};
          const uint32_t I[4] = {pack2(0.f, z8.i), pack2(q2.i, q3.i), pack2(q4.i, q5.i), pack2(q6.i, q7.i)};
          sts128(st_a, R[0], R[1], R[2], R[3]);
          sts128(st_a + 512, I[0], I[1], I[2], I[3]);
          {
            const cf m64 = cmul(q4, q4);
            const uint32_t mp = pack2(m64.r, m64.i);
            const uint32_t ma = stg + 1024 + (((lane >> 1) & 3) * 8 + (lane >> 3) * 2 + (lane & 1)) * 2;
            sts16(ma, (uint16_t)mp); sts16(ma + 64, (uint16_t)(mp >> 16));
          }
          __syncwarp();
          uint32_t A0[4][4], A1[4][4];
          {
            const uint4 mr4 = lds128(stg + 1024 + t * 16), mi4 = lds128(stg + 1088 + t * 16);
            const uint32_t mr[4] = {mr4.x, mr4.y, mr4.z, mr4.w}, mi[4] = {mi4.x, mi4.y, mi4.z, mi4.w};
#pragma unroll
            for (int kp = 0; kp < 2; kp++) ldsm4t(ld_c - 4096 + kp * 256, A0[2 * kp][0], A0[2 * kp][2], A0[2 * kp + 1][0], A0[2 * kp + 1][2]);
#pragma unroll
            for (int ks = 0; ks < 4; ks++) {
              const uint32_t ni = mi[ks] ^ 0x80008000u;
              A0[ks][1] = hfma2(A0[ks][0], mr[ks], hmul2(A0[ks][2], ni)); A0[ks][3] = hfma2(A0[ks][0], mi[ks], hmul2(A0[ks][2], mr[ks]));
              A1[ks][0] = hfma2(A0[ks][1], mr[ks], hmul2(A0[ks][3], ni)); A1[ks][2] = hfma2(A0[ks][1], mi[ks], hmul2(A0[ks][3], mr[ks]));
              A1[ks][1] = hfma2(A1[ks][0], mr[ks], hmul2(A1[ks][2], ni)); A1[ks][3] = hfma2(A1[ks][0], mi[ks], hmul2(A1[ks][2], mr[ks]));
            }
          }
#define KG_TILE(nt) do { __syncwarp(); \
            _Pragma("unroll") for (int kp = 0; kp < 2; kp++) { uint32_t c6[4]; \
              ldsm4t(ld_c + (nt) * 1024 + kp * 256, c6[0], c6[1], c6[2], c6[3]); \
              _Pragma("unroll") for (int k2 = 0; k2 < 2; k2++) { const int ks = 2 * kp + k2; \
                mma16816(kacc[0][nt], A0[ks][0], A0[ks][1], A0[ks][2], A0[ks][3], c6[2 * k2], c6[2 * k2 + 1]); \
                mma16816(kacc[1][nt], A1[ks][0], A1[ks][1], A1[ks][2], A1[ks][3], c6[2 * k2], c6[2 * k2 + 1]); } } } while (0)
          const cf a0 = cmul(w, z256), b0 = cmul(a0, z256), z512 = cmul(z256, z256);
          const cf c0 = cmul(a0, z512), d0 = cmul(b0, z512), d1 = cmul(c0, z512), d2 = cmul(d0, z512), d3 = cmul(d1, z512), d4 = cmul(d2, z512);
          sts128(st_a + 12 * 512, pack2(d0.r, d1.r), pack2(d2.r, d3.r), pack2(d4.r, 0.f), 0);
          sts128(st_a + 13 * 512, pack2(d0.i, d1.i), pack2(d2.i, d3.i), pack2(d4.i, 0.f), 0);
          KG_TILE(2);
          const cf z2 = cmul(z1, z1);
          const cf p1 = cmul(w, z1), p2 = cmul(w, z2), p3 = cmul(p1, z2), p4 = cmul(p2, z2), p5 = cmul(p3, z2), p6 = cmul(p4, z2), p7 = cmul(p5, z2);
          sts128(st_a + 8 * 512, pack2(w.r, p1.r), pack2(p2.r, p3.r), pack2(p4.r, p5.r), pack2(p6.r, p7.r));
          sts128(st_a + 9 * 512, pack2(w.i, p1.i), pack2(p2.i, p3.i), pack2(p4.i, p5.i), pack2(p6.i, p7.i));
          KG_TILE(0);
          const cf a1 = cmul(p2, z256), a2_ = cmul(p4, z256), a3 = cmul(p6, z256), b1 = cmul(p4, z512), c1 = cmul(a2_, z512);
          sts128(st_a + 10 * 512, pack2(a0.r, a1.r), pack2(a2_.r, a3.r), pack2(b0.r, b1.r), pack2(c0.r, c1.r));
          sts128(st_a + 11 * 512, pack2(a0.i, a1.i), pack2(a2_.i, a3.i), pack2(b0.i, b1.i), pack2(c0.i, c1.i));
          KG_TILE(1);
          __syncwarp();
          }
          const uint32_t kp = stg + (ph ? 4096 : 1152) + (2 * t * 36 + g) * 4;
#pragma unroll
          for (int mt = 0; mt < 2; mt++)
#pragma unroll
            for (int nt = 0; nt < 3; nt++)
#pragma unroll
              for (int e = 0; e < 4; e++) if (nt < 2 || t < 2 || (mt == 0 && e == 0 && lane == 2)) stsf(kp + ((nt * 8 + (e & 1)) * 36 + mt * 16 + (e >> 1) * 8) * 4, kacc[mt][nt][e]);
          continue;
        }
        if (ph == 2) asm volatile("bar.sync %0, 128;" ::"r"(2 + wg) : "memory");
        build_tables(sb, lut, wg, ph - 2);
        if (ph == 3) asm volatile("bar.arrive 0, 288;" ::: "memory");
        asm volatile("bar.sync %0, 256;" ::"r"(ph == 2 ? 6 + wg : 4 + wg) : "memory");
        if (ph == 2 && wg == 1) {
#pragma unroll 1
          for (int k = warp & 3; k < 7; k += 4) step2_item(sb, 4 * k + 1, lane);
          asm volatile("bar.sync 3, 128;" ::: "memory");
        }
        const int rnd = ph - 2;
        const int ch = 2 * rnd + wg, hv = warp & 1;
        const bool heavy = (((warp >> 1) ^ wg) & 1) == 0;
        const int grp = heavy ? 3 - hv : hv;
        const int a0 = 4 * grp;
        const uint32_t ub = sb + SM_U + ch * U_CH + U_PAD * 16;
        const uint32_t g_far = g_far0 + ch * STAGE;
        const uint32_t fb0 = sb + SM_FAR + ch * STAGE + (16 * (lane >> 4) + 15 - (lane & 15)) * 16;
        const uint32_t cm0 = sb + SM_FAR + ch * STAGE + (hv ? FAR_U5 : FAR_B7 + 64) * 16 + lane * 16;
        const uint32_t cm1 = sb + (hv ? SM_CMB + ch * 1024 : SM_FAR + ch * STAGE + (FAR_B9 + 64) * 16) + lane * 16;
        float acc[4][4];
#pragma unroll
        for (int i = 0; i < 16; i++) (&acc[0][0])[i] = 0.f;
        if (!heavy) {
          if (hv) far_far<2>(acc, fb0 + 2048, g_far, z);
          else far_far<3>(acc, fb0 + 3072, g_far, z);
#pragma unroll
          for (int i = 0; i < 4; i++) {
            sts128((i < 2 ? cm0 : cm1) + (i & 1) * 512, __float_as_uint(acc[i][0]), __float_as_uint(acc[i][1]), __float_as_uint(acc[i][2]), __float_as_uint(acc[i][3]));
#pragma unroll
            for (int k = 0; k < 4; k++) acc[i][k] = 0.f;
          }
          asm volatile("bar.arrive %0, 64;" ::"r"(8 + 2 * ch + hv) : "memory");
        }
        {
          const uint32_t ha = ub + (16 * a0 - 33 + ((lane >> 3) & 1) * 8 + (lane >> 4) + (lane & 7)) * 16;
          const uint32_t ga = g_near + ch * STAGE;
#pragma unroll
          for (int sg = 0; sg < 4; sg++) {
            uint32_t Q[6][4], G[5][2];
#pragma unroll
            for (int q = 5; q >= 0; q--) ldsm4(ha - sg * 32 + q * 256, Q[q][0], Q[q][1], Q[q][2], Q[q][3]);
#pragma unroll
            for (int S = 0; S < 5; S++) if (S < 4 || sg == 0) { G[S][0] = lds32(ga - sg * 32 - S * 128 - 16); G[S][1] = lds32(ga - sg * 32 - S * 128); }
#pragma unroll
            for (int i = 3; i >= 0; i--) mma16816(acc[i], Q[i + 2][0], Q[i + 2][1], Q[i + 2][2], Q[i + 2][3], G[0][0], G[0][1]);
#pragma unroll
            for (int i = 3; i >= 0; i--) mma16816(acc[i], Q[i + 1][0], Q[i + 1][1], Q[i + 1][2], Q[i + 1][3], G[2][0], G[2][1]);
            if (sg == 0) {
#pragma unroll
              for (int i = 3; i >= 0; i--) mma16816(acc[i], Q[i][0], Q[i][1], Q[i][2], Q[i][3], G[4][0], G[4][1]);
            }
            uint32_t O[5][4];
#pragma unroll
            for (int q = 0; q < 5; q++) { O[q][0] = Q[q][1] + z; O[q][1] = Q[q + 1][0] + z; O[q][2] = Q[q][3] + z; O[q][3] = Q[q + 1][2] + z; }
#pragma unroll
            for (int i = 3; i >= 0; i--) mma16816(acc[i], O[i + 1][0], O[i + 1][1], O[i + 1][2], O[i + 1][3], G[1][0], G[1][1]);
#pragma unroll
            for (int i = 3; i >= 0; i--) mma16816(acc[i], O[i][0], O[i][1], O[i][2], O[i][3], G[3][0], G[3][1]);
          }
        }
        {
          const uint32_t fb = fb0 + grp * 1024;
          if (heavy) far_mid<2>(acc, fb, g_far, z);
          else if (hv) far_mid<1>(acc, fb, g_far, z);
          else far_mid<0>(acc, fb, g_far, z);
          if (heavy) {
            asm volatile("bar.sync %0, 64;" ::"r"(8 + 2 * ch + hv) : "memory");
#pragma unroll
            for (int i = 0; i < 4; i++) {
              const uint4 c4 = lds128((i < 2 ? cm0 : cm1) + (i & 1) * 512);
              acc[i][0] += __uint_as_float(c4.x); acc[i][1] += __uint_as_float(c4.y); acc[i][2] += __uint_as_float(c4.z); acc[i][3] += __uint_as_float(c4.w);
            }
          }
        }
        {
          mbar_wait(bar + 8 * B_XT, 0);
          const uint32_t dsk = __byte_perm(rnd ? dskraw.y : dskraw.x, 0, wg ? 0x3232 : 0x1010);
#pragma unroll
          for (int i2 = 0; i2 < 2; i2++) {
            uint32_t xr[4], ur[4];
            const uint32_t xa = sb + SM_X + ch * X_CH + (16 * a0 + 32 * i2 + lane) * 16;
            ldsm4(ub + (16 * a0 + 32 * i2 + lane) * 16, ur[0], ur[1], ur[2], ur[3]);
            ldsm4(xa, xr[0], xr[1], xr[2], xr[3]);
#pragma unroll
            for (int k = 0; k < 4; k++) {
              const uint32_t yb = pack2(acc[2 * i2 + (k >> 1)][2 * (k & 1)], acc[2 * i2 + (k >> 1)][2 * (k & 1) + 1]);
              xr[k] = hadd2(xr[k], hadd2(yb, hmul2(ur[k], dsk)));
            }
            stsm4(xa, xr[0], xr[1], xr[2], xr[3]);
          }
          asm volatile("fence.proxy.async.shared::cta;" ::: "memory");
        }
        __syncwarp();
        if (lane == 0) mbar_arrive(bar + 8 * (B_CH + rnd));
      }
    } else {
      const int f = b & 7;
      asm volatile("bar.sync 4, 384;" ::: "memory");
      if (tid == 224) {
        mbar_expect(bar + 8 * B_X, 7 * STAGE);
#pragma unroll 1
        for (int i = 0; i < 14; i++) tma2d(sb + i * 14336, (b & 8) ? &tm_wu64 : &tm_wg64, 224 * f + 32 * (i >> 1), 224 * (i & 1), bar + 8 * B_X);
      }
      if (warp < 7) {
        const uint32_t a = sb + warp * STAGE + g * 64 + ((t ^ (g >> 1)) & 3) * 16;
        float s[8];
#pragma unroll
        for (int i = 0; i < 8; i++) s[i] = 0.f;
        mbar_wait(bar + 8 * B_X, 0);
#pragma unroll 4
        for (int i = 0; i < 56; i++) {
          const uint4 w4 = lds128(a + i * 512);
          s[0] += blo(w4.x); s[1] += bhi(w4.x); s[2] += blo(w4.y); s[3] += bhi(w4.y);
          s[4] += blo(w4.z); s[5] += bhi(w4.z); s[6] += blo(w4.w); s[7] += bhi(w4.w);
        }
#pragma unroll
        for (int lv = 0; lv < 3; lv++) {
          const int h = 4 >> lv;
          const bool up = lane & (4 * h);
#pragma unroll
          for (int i = 0; i < 4; i++) if (i < h) {
            const float keep = up ? s[i + h] : s[i], send = up ? s[i] : s[i + h];
            s[i] = keep + __shfl_xor_sync(~0u, send, 4 * h);
          }
        }
        st_relaxed8(&p.s->cs[(b - NCONV) * 224 + warp * 32 + t * 8 + g], __float_as_uint(s[0]), EPOCH);
      }
      asm volatile("bar.sync 8, 384;" ::: "memory");
    }
    asm volatile("setmaxnreg.inc.sync.aligned.u32 232;");
    asm volatile("barrier.cluster.wait.aligned;" ::: "memory");

    FRESH_IDS
    int tid; asm volatile("mov.u32 %0, %%tid.x;" : "=r"(tid));
    const int lane = tid & 31, g = lane >> 2, t = lane & 3;
    const int warp = __shfl_sync(~0u, tid >> 5, 0);
    const int wgi = warp >> 2;
    const uint32_t dA = ((SMEM_BASE + SM_A) >> 4) + wgi * (14336 >> 4) + (1u << 16);
    constexpr uint32_t dB = (SMEM_BASE >> 4) | ((14336u >> 4) << 16);
    uint32_t peer;
    asm volatile("mapa.shared::cluster.u32 %0, %1, %2;" : "=r"(peer) : "r"(sb), "r"(ra ^ 1));
    float X[64], Y[64], Z[32];
    uint32_t ho[56], hp[56];
    uint32_t nm0 = 0, nm1 = 0;
    uint32_t res[16], rdep = 0;
    const int col0 = 224 * ra + 56 * sp;

#define STAGE_WAIT(i) mbar_wait(bar + 8 * (B_FULL + st_slot(i)), st_use(i) & 1)
#define STAGE_REL(i) do { if (st_rel(i) && lane == 0) mbar_arrive(bar + 8 * (B_EMPTY + st_slot(i)) + ((i) == 11 ? rdep : 0)); \
    if ((i) == 3 && lane == 0) mbar_arrive_remote(peer + SM_BAR + 8 * B_FREE); } while (0)
#define TURN_WAIT() asm volatile("bar.sync %0, 256;" ::"r"(6 + wgi) : "memory")
#define TURN_PASS() asm volatile("bar.arrive %0, 256;" ::"r"(7 - wgi) : "memory")
#define W128(ACC, i, q, kk, SC) wgmma_ss_n128<DESC_HI128, SC>(ACC, dA + (((q) * STAGE) >> 4) + (kk) * 128, dB + (st_addr(i) >> 4) + (kk) * 128)
#define DONE(i) do { wg_wait<0>(); STAGE_REL(i); } while (0)
#define STAGE128(ACC, i, q, first) do { STAGE_WAIT(i); TURN_WAIT(); wg_fence(); \
    if ((i) == 8) { AUG(128, X, 0); AUG(64, Z, 3); } if ((i) == 9) AUG(128, Y, 1); if ((i) == 11) AUG(128, X, 2); \
    W128(ACC, i, q, 0, (first) ? 0 : 1); \
    _Pragma("unroll") for (int kk = 1; kk < 7; kk++) W128(ACC, i, q, kk, 1); \
    wg_commit(); TURN_PASS(); } while (0)
#define AUG(N, ACC, J) wgmma_aug_n##N(ACC, t == (J) ? nm0 : 0u, t == (J) ? nm1 : 0u, p.zero, ((SMEM_BASE + SM_CS) >> 4) | ((1024u >> 4) << 16))
#define EPI(ACC, NG, O) do { reg_fence(ACC); \
    _Pragma("unroll") for (int j = 0; j < NG; j++) { \
      ho[(O) + 2 * j] = pack2(ACC[4 * j] * ACC[4 * NG + 4 * j], ACC[4 * j + 1] * ACC[4 * NG + 4 * j + 1]); \
      ho[(O) + 2 * j + 1] = pack2(ACC[4 * j + 2] * ACC[4 * NG + 4 * j + 2], ACC[4 * j + 3] * ACC[4 * NG + 4 * j + 3]); \
    } } while (0)
#define SEND(O, NV, MB, BARI) do { \
    _Pragma("unroll") for (int vv = 0; vv < NV; vv++) \
      asm volatile("st.async.weak.shared::cluster.mbarrier::complete_tx::bytes.v4.b32 [%0], {%1,%2,%3,%4}, [%5];" \
        ::"r"(peer + (MB) + (warp * NV + vv) * 512 + lane * 16), "r"(ho[(O) + 4 * vv]), "r"(ho[(O) + 4 * vv + 1]), "r"(ho[(O) + 4 * vv + 2]), \
          "r"(ho[(O) + 4 * vv + 3]), "r"(peer + SM_BAR + 8 * (BARI)) : "memory"); } while (0)
#define RECV(O, NV, MB, BARI, PH, UNUSED) do { mbar_wait(bar + 8 * (BARI), PH); \
    _Pragma("unroll") for (int vv = 0; vv < NV; vv++) { const uint4 r4 = lds128(sb + (MB) + (warp * NV + vv) * 512 + lane * 16); \
      hp[(O) + 4 * vv] = r4.x; hp[(O) + 4 * vv + 1] = r4.y; hp[(O) + 4 * vv + 2] = r4.z; hp[(O) + 4 * vv + 3] = r4.w; } \
    } while (0)
#define REARM(O) do { const uint32_t dep = (hp[O] ^ hp[(O) + 4] ^ hp[(O) + 8] ^ hp[(O) + 12]) & p.zero;     \
      if (tid == 0) mbar_expect(bar + 8 * B_MBF0, 16384); \
      if (lane == 0) mbar_arrive_remote(peer + SM_BAR + 8 * B_FREE + dep); } while (0)
#define W64(i, hh, kk, SC) wgmma_ss_n64<DESC_HI64, SC>(Z, dA + (((2 * (hh) + (kk) / 7) * STAGE) >> 4) + ((kk) % 7) * 128, dB + (st_addr(i) >> 4) + (kk) * 64)
#define STAGE64(i, hh) do { STAGE_WAIT(i); TURN_WAIT(); wg_fence(); W64(i, hh, 0, (hh) == 0 ? 0 : 1); \
    _Pragma("unroll") for (int kk = 1; kk < 14; kk++) W64(i, hh, kk, 1); \
    wg_commit(); TURN_PASS(); } while (0)

    mbar_wait(bar + 8 * (B_AFULL + 0), 0);
    if (wgi == 1) TURN_PASS();
    STAGE128(X, 0, 0, true); DONE(0);
    mbar_wait(bar + 8 * (B_AFULL + 1), 0);
    STAGE64(1, 0); DONE(1);
    STAGE128(X, 2, 1, false); DONE(2);
    STAGE128(Y, 3, 0, true); DONE(3);
    STAGE128(Y, 4, 1, false); DONE(4);
    mbar_wait(bar + 8 * (B_AFULL + 2), 0);
    STAGE128(X, 5, 2, false); DONE(5);
    mbar_wait(bar + 8 * (B_AFULL + 3), 0);
    STAGE128(X, 6, 3, false);
    mbar_wait(bar + 8 * B_FREE, 0);
    DONE(6);
    STAGE64(7, 1);
    DONE(7);
    mbar_wait(bar + 8 * B_AUX, 0);
    { uint16_t m0, m1;
      asm volatile("ld.shared.u16 %0, [%1];" : "=h"(m0) : "r"(sb + SM_M2 + (16 * warp + g) * 2) : "memory");
      asm volatile("ld.shared.u16 %0, [%1];" : "=h"(m1) : "r"(sb + SM_M2 + (16 * warp + g + 8) * 2) : "memory");
      nm0 = (uint32_t)m0 * 0x10001u; nm1 = (uint32_t)m1 * 0x10001u; }
    STAGE128(Y, 8, 2, false);
    DONE(8);
    EPI(X, 8, 8);
    SEND(8, 4, SM_MB0, B_MBF0);
    STAGE128(Y, 9, 3, false);
    EPI(Z, 4, 0);
    SEND(0, 2, SM_MB1, B_MBF1);
    DONE(9);
    STAGE128(X, 10, 0, true);
    RECV(8, 4, SM_MB0, B_MBF0, 0, false);
    EPI(Y, 8, 24);
    REARM(8);
    DONE(10);
    STAGE128(X, 11, 1, false);
#pragma unroll
    for (int j2 = 0; j2 < 4; j2++) {
      const int kl = 56 * (sp & 1) + 16 * j2 + (j2 == 3 ? 0 : (lane >> 4) * 8) + (lane & 7);
      const uint32_t addr = sb + SM_A + (2 * ra + (sp >> 1)) * STAGE + wgi * 14336 + kl * 128 + (((2 * (warp & 3) + ((lane >> 3) & 1)) ^ (lane & 7)) * 16);
      ldsm4t(addr, res[4 * j2], res[4 * j2 + 1], res[4 * j2 + 2], res[4 * j2 + 3]);
    }
    mbar_wait(bar + 8 * B_FREE, 1);
    SEND(24, 4, SM_MB0, B_MBF0);
    rdep = (res[0] ^ res[4] ^ res[8] ^ res[12]) & p.zero;
    if (tid == 0) mbar_expect(bar + 8 * B_AFULL, 16384);
    if (lane == 0) mbar_arrive_remote(peer + SM_BAR + 8 * B_CH + rdep);
    DONE(11);
    STAGE128(X, 12, 2, false);
    RECV(0, 2, SM_MB1, B_MBF1, 0, false);
#pragma unroll
    for (int j2 = 0; j2 < 3; j2++)
      sts128(sb + SM_MB1 + (j2 < 2 ? (warp * 2 + j2) * 512 : 8192 + warp * 512) + lane * 16, res[4 * j2], res[4 * j2 + 1], res[4 * j2 + 2], res[4 * j2 + 3]);
    DONE(12);
    STAGE128(X, 13, 3, false);
    RECV(24, 4, SM_MB0, B_MBF0, 1, false);
    DONE(13);
    EPI(X, 8, 40);
    mbar_wait(bar + 8 * B_CH, conv_cta ? 1 : 0);
    SEND(40, 4, SM_A, B_AFULL);
    float OP[28], OQ[28];
    const uint32_t tag = TAG;
#define W56(ACC, i, half, kk) do { const int a = 4 * (7 * (half) + ((kk) % 7)); \
      const uint32_t db = ((SMEM_BASE + st_addr(i) + (kk) * 1792) >> 4) | ((128u >> 4) << 16); \
      if ((kk) == 0 && (half) == 0) wgmma_rs_n56<0>(ACC, ho[a], ho[a + 1], ho[a + 2], ho[a + 3], db); \
      else if ((kk) < 7) wgmma_rs_n56<1>(ACC, ho[a], ho[a + 1], ho[a + 2], ho[a + 3], db); \
      else wgmma_rs_n56<1>(ACC, hp[a], hp[a + 1], hp[a + 2], hp[a + 3], db); } while (0)
#define STAGE56(ACC, i, half) do { STAGE_WAIT(i); TURN_WAIT(); wg_fence(); \
    _Pragma("unroll") for (int kk = 0; kk < 14; kk++) W56(ACC, i, half, kk); \
    wg_commit(); if ((i) < 21 || wgi == 0) TURN_PASS(); } while (0)
#define SENDP4(ACC, XM) do { SENDP(ACC, XM, 0); SENDP(ACC, XM, 1); SENDP(ACC, XM, 2); SENDP(ACC, XM, 3); } while (0)
#define SENDP(ACC, XM, vv) do { if ((vv) == 0) reg_fence(ACC); \
    uint4* dstp = p.s->part + (size_t)(b ^ (2 * (XM))) * 3072 + ((XM) - 1) * 1024 + warp * 128 + lane; \
      st_relaxed_b128(dstp + (vv) * 32, pack2(ACC[7 * (vv)], ACC[7 * (vv) + 1]), pack2(ACC[7 * (vv) + 2], ACC[7 * (vv) + 3]), \
                      pack2(ACC[7 * (vv) + 4], ACC[7 * (vv) + 5]), (pack2(ACC[7 * (vv) + 6], 0.f) & 0xffffu) | (tag << 16)); } while (0)
    STAGE56(OP, 14, 0); DONE(14);
    STAGE56(OQ, 15, 0);
    RECV(40, 4, SM_A, B_AFULL, 1, false);
    STAGE56(OP, 16, 1); DONE(16);
    SENDP4(OP, 2);
    STAGE56(OQ, 17, 1); DONE(17);
    SENDP4(OQ, 3);
    STAGE56(OP, 18, 0);
    STAGE56(OP, 19, 1); DONE(19);
    SENDP4(OP, 1);
    STAGE56(OQ, 20, 0);
    float ps[28];
    const uint4* srcp = p.s->part + (size_t)b * 3072 + warp * 128 + lane;
    {
      uint4 pv[8]; uint32_t it = 0; bool ok;
      do {
        ok = true;
#pragma unroll
        for (int k = 0; k < 8; k++) pv[k] = ld_relaxed_b128(srcp + 1024 + (k >> 2) * 1024 + (k & 3) * 32);
#pragma unroll
        for (int k = 0; k < 8; k++) ok = ok && (pv[k].w >> 16) == tag;
        SPIN_CHECK(it);
      } while (!ok);
#pragma unroll
      for (int k = 0; k < 4; k++) {
        const int o = 7 * k;
        ps[o] = blo(pv[k].x) + blo(pv[k + 4].x); ps[o + 1] = bhi(pv[k].x) + bhi(pv[k + 4].x);
        ps[o + 2] = blo(pv[k].y) + blo(pv[k + 4].y); ps[o + 3] = bhi(pv[k].y) + bhi(pv[k + 4].y);
        ps[o + 4] = blo(pv[k].z) + blo(pv[k + 4].z); ps[o + 5] = bhi(pv[k].z) + bhi(pv[k + 4].z);
        ps[o + 6] = blo(pv[k].w) + blo(pv[k + 4].w);
      }
      __syncwarp();
    }
#pragma unroll
    for (int j2 = 0; j2 < 3; j2++) { const uint4 r4 = lds128(sb + SM_MB1 + (j2 < 2 ? (warp * 2 + j2) * 512 : 8192 + warp * 512) + lane * 16); res[4 * j2] = r4.x; res[4 * j2 + 1] = r4.y; res[4 * j2 + 2] = r4.z; res[4 * j2 + 3] = r4.w; }
    res[14] = 0; res[15] = 0;
    const float r0 = ldsf(sb + SM_RS2 + (16 * warp + g) * 4), r1 = ldsf(sb + SM_RS2 + (16 * warp + g + 8) * 4);
    STAGE56(OQ, 21, 1); DONE(21);
    reg_fence(OQ);
    {
      uint4 pv[4]; uint32_t it = 0; bool ok;
      do {
        ok = true;
#pragma unroll
        for (int k = 0; k < 4; k++) pv[k] = ld_relaxed_b128(srcp + k * 32);
        if (it == 0) {
#pragma unroll
          for (int i = 0; i < 28; i++) ps[i] += OQ[i];
        }
#pragma unroll
        for (int k = 0; k < 4; k++) ok = ok && (pv[k].w >> 16) == tag;
        SPIN_CHECK(it);
      } while (!ok);
#pragma unroll
      for (int k = 0; k < 4; k++) {
        const int o = 7 * k;
        ps[o] += blo(pv[k].x); ps[o + 1] += bhi(pv[k].x); ps[o + 2] += blo(pv[k].y); ps[o + 3] += bhi(pv[k].y);
        ps[o + 4] += blo(pv[k].z); ps[o + 5] += bhi(pv[k].z); ps[o + 6] += blo(pv[k].w);
      }
      __syncwarp();
    }
#pragma unroll
    for (int j = 0; j < 7; j++) {
      res[2 * j] = hadd2(res[2 * j], pack2(ps[4 * j] * r0, ps[4 * j + 1] * r0));
      res[2 * j + 1] = hadd2(res[2 * j + 1], pack2(ps[4 * j + 2] * r1, ps[4 * j + 3] * r1));
    }
    const uint32_t ost = sb + SM_MB0 + warp * 2048;
#pragma unroll
    for (int j2 = 0; j2 < 4; j2++) {
      uint32_t addr = ost + (lane & 15) * 112 + (2 * j2 + (lane >> 4)) * 16;
      if (j2 == 3 && lane >= 16) addr = ost + 1792 + (lane & 15) * 16;
      stsm4(addr, res[4 * j2], res[4 * j2 + 1], res[4 * j2 + 2], res[4 * j2 + 3]);
    }
    __syncwarp();
    char* op = (char*)p.out + (size_t)(128 * rt + 16 * warp) * (D_ * 2) + col0 * 2;
#pragma unroll
    for (int k = 0; k < 4; k++) {
      const int idx = lane + 32 * k;
      if (idx < 112) {
        const int row = (idx * 147) >> 10, c = idx - 7 * row;
        const uint4 ov = lds128(ost + idx * 16);
        *(uint4*)(op + row * (D_ * 2) + c * 16) = ov;
      }
    }
  }
}

typedef CUresult (*EncodeFn)(CUtensorMap*, CUtensorMapDataType, cuuint32_t, void*, const cuuint64_t*, const cuuint64_t*,
                             const cuuint32_t*, const cuuint32_t*, CUtensorMapInterleave, CUtensorMapSwizzle,
                             CUtensorMapL2promotion, CUtensorMapFloatOOBfill);

extern "C" void kernel_launch(void* const* d_in, const int* in_sizes, int n_in, void* d_out, int out_size) {
  (void)in_sizes; (void)n_in; (void)out_size;
  static EncodeFn enc = nullptr;
  static void *scr = nullptr, *lut = nullptr;
  if (!enc) {
    void* fn = nullptr; cudaDriverEntryPointQueryResult qr;
    cudaGetDriverEntryPoint("cuTensorMapEncodeTiled", &fn, cudaEnableDefault, &qr);
    enc = (EncodeFn)fn;
    cudaGetSymbolAddress(&scr, g_s);
    cudaGetSymbolAddress(&lut, g_lut);
    cudaFuncSetAttribute(fused_kernel, cudaFuncAttributeMaxDynamicSharedMemorySize, SM_TOTAL);
  }
  Params p;
  p.x = (const __nv_bfloat16*)d_in[0];
  p.Are = (const __nv_bfloat16*)d_in[1]; p.Aim = (const __nv_bfloat16*)d_in[2];
  p.Bre = (const __nv_bfloat16*)d_in[3]; p.Bim = (const __nv_bfloat16*)d_in[4];
  p.Cre = (const __nv_bfloat16*)d_in[5]; p.Cim = (const __nv_bfloat16*)d_in[6];
  p.logdt = (const __nv_bfloat16*)d_in[7]; p.dskip = (const __nv_bfloat16*)d_in[8];
  p.s = (Scratch*)scr; p.lut = (const uint32_t*)lut; p.zero = 0;
  p.out = (__nv_bfloat16*)d_out; p.wd = (const __nv_bfloat16*)d_in[12];
  CUtensorMap m[6];
  const cuuint32_t es[3] = {1, 1, 1};
  for (int i = 0; i < 4; i++) {
    const cuuint64_t dims[2] = {(cuuint64_t)F_, (cuuint64_t)D_};
    const cuuint64_t str[1] = {(cuuint64_t)F_ * 2};
    const cuuint32_t box128[2] = {64, 112}, box64[2] = {32, 224};
    enc(&m[i], CU_TENSOR_MAP_DATA_TYPE_BFLOAT16, 2, d_in[10 + (i & 1)], dims, str, i < 2 ? box128 : box64, es,
        CU_TENSOR_MAP_INTERLEAVE_NONE, i < 2 ? CU_TENSOR_MAP_SWIZZLE_128B : CU_TENSOR_MAP_SWIZZLE_64B,
        CU_TENSOR_MAP_L2_PROMOTION_L2_128B, CU_TENSOR_MAP_FLOAT_OOB_FILL_NONE);
  }
  {
    const cuuint64_t dims[3] = {8, (cuuint64_t)F_, (cuuint64_t)D_ / 8}; const cuuint64_t str[2] = {(cuuint64_t)D_ * 2, 16};
    const cuuint32_t box[3] = {8, 16, 7};
    enc(&m[4], CU_TENSOR_MAP_DATA_TYPE_BFLOAT16, 3, d_in[12], dims, str, box, es, CU_TENSOR_MAP_INTERLEAVE_NONE,
        CU_TENSOR_MAP_SWIZZLE_NONE, CU_TENSOR_MAP_L2_PROMOTION_L2_128B, CU_TENSOR_MAP_FLOAT_OOB_FILL_NONE);
  }
  {
    const cuuint64_t dims[2] = {(cuuint64_t)L_, (cuuint64_t)D_}; const cuuint64_t str[1] = {(cuuint64_t)L_ * 2};
    const cuuint32_t box[2] = {64, 112};
    enc(&m[5], CU_TENSOR_MAP_DATA_TYPE_BFLOAT16, 2, (void*)p.s->hT, dims, str, box, es, CU_TENSOR_MAP_INTERLEAVE_NONE,
        CU_TENSOR_MAP_SWIZZLE_128B, CU_TENSOR_MAP_L2_PROMOTION_L2_128B, CU_TENSOR_MAP_FLOAT_OOB_FILL_NONE);
  }
  fused_kernel<<<NCTA, NTHR, SM_TOTAL, cudaStreamPerThread>>>(p, m[0], m[1], m[2], m[3], m[4], m[5]);
}
```
